```python
import torch

def _softmax(x, axis=-1):
    return torch.softmax(x, dim=axis)
def _gelu(x):
    return torch.nn.functional.gelu(x, approximate="tanh")
def _silu(x):
    return torch.nn.functional.silu(x)
def _sigmoid(x):
    return torch.sigmoid(x)
def _layernorm(x, axis=-1, eps=1e-5):
    m = x.mean(dim=axis, keepdim=True)
    v = x.var(dim=axis, keepdim=True, unbiased=False)
    return (x - m) / torch.sqrt(v + eps)
def _scatter_add(tgt, idx, src, axis=0):
    return tgt.clone().index_add_(axis, idx, src)
def _segment_sum(src, seg, n):
    out = torch.zeros((n,) + src.shape[1:], dtype=src.dtype)
    return out.index_add_(0, seg, src)
def _pad(x, pw):
    flat = tuple(v for pair in reversed(pw) for v in pair)
    return torch.nn.functional.pad(x, flat)

kernel_name = 'gated_mix__spectral_gfnet__mixer_token_mlp__prompt'

def setup_inputs():

    _w = (lambda a: (lambda t: t.to(torch.bfloat16) if t.is_floating_point() else t)(torch.as_tensor(a)))
    def _A_setup():
        B, S, D = 1, 2048, 576
        Df = D // 2 + 1
        return {
            "x": _w((lambda *s: torch.randn(*s, dtype=torch.bfloat16) * 0.05)(B, S, D)),
            "w_r": _w((lambda *s: torch.randn(*s, dtype=torch.bfloat16) * 1.6)(S, Df) * 0.02),
            "w_i": _w((lambda *s: torch.randn(*s, dtype=torch.bfloat16) * 1.6)(S, Df) * 0.02),
        }
    _A_in = _A_setup()

    def _B_setup():
        B, S, D, F = 1, 2048, 576, 4608
        return {
            "x": _w((lambda *s: torch.randn(*s, dtype=torch.bfloat16) * 0.05)(B, S, D)),
            "w1": _w((lambda *s: torch.randn(*s, dtype=torch.bfloat16) * 0.2)(S, F) * (S ** -0.5)),
            "b1": _w((lambda *s: torch.randn(*s, dtype=torch.bfloat16) * 3.2)(F) * 0.02),
            "w2": _w((lambda *s: torch.randn(*s, dtype=torch.bfloat16) * 0.05)(F, S) * (F ** -0.5)),
            "b2": _w((lambda *s: torch.randn(*s, dtype=torch.bfloat16) * 0.1)(S) * 0.02),
        }
    _B_in = _B_setup()

    return {
        "A_x": _A_in["x"],
        "A_w_r": _A_in["w_r"],
        "A_w_i": _A_in["w_i"],
        "B_x": _B_in["x"],
        "B_w1": _B_in["w1"],
        "B_b1": _B_in["b1"],
        "B_w2": _B_in["w2"],
        "B_b2": _B_in["b2"],
        "gate_w": _w((lambda *s: torch.randn(*s, dtype=torch.bfloat16) * 0.05)(576) * 16.0),
    }

def reference(A_x, A_w_r, A_w_i, B_x, B_w1, B_b1, B_w2, B_b2, gate_w):
    def _A_ref(x, w_r, w_i):
        B, S, D = x.shape
        X = (lambda x, axes=(-2,-1): torch.fft.rfft2(x.float(), dim=axes))(x, axes=(-2, -1))
        W = w_r + 1j * w_i
        X = X * W
        y = (lambda x, s, axes=(-2,-1): torch.fft.irfft2(x, s=s, dim=axes).to(torch.bfloat16))(X, (S, D), axes=(-2, -1))
        return y

    def _B_ref(x, w1, b1, w2, b2):
        B, S, D = x.shape
        h = _layernorm(x, axis=-1)
        u = torch.einsum("bsd,sf->bdf", h, w1) + b1
        u = _gelu(u)
        y = torch.einsum("bdf,fs->bds", u, w2) + b2
        return (lambda x, *d: x.permute(*d))(y, 0, 2, 1)

    x = A_x
    g = _sigmoid((x * gate_w).sum(-1, keepdims=True))
    a = _A_ref(x, A_w_r, A_w_i)
    b = _B_ref(x, B_w1, B_b1, B_w2, B_b2)
    return g * a + (1 - g) * b
```

```cpp
#include <cuda_runtime.h>
#include <cuda_bf16.h>
#include <cuda.h>
#include <stdint.h>

namespace gm {

constexpr int NCTA = 132;
constexpr uint32_t ST1 = 40960;
constexpr uint32_t ST2 = 34816;
constexpr uint32_t OFF_TAB = 0;
constexpr uint32_t OFF_WCOL = 34816;
constexpr uint32_t OFF_WSR = 3 * ST1;
constexpr uint32_t OFF_HST = ST1 + 16384;
constexpr uint32_t OFF_CTAB = 40960;
constexpr uint32_t OFF_XCOL = 133120;
constexpr uint32_t OFF_TWA = 169472;
constexpr uint32_t OFF_FFT = 174080;
constexpr uint32_t OFF_EXCH = OFF_FFT;
constexpr uint32_t OFF_RAW = OFF_FFT + 36992;
constexpr uint32_t OFF_XST = OFF_FFT;
constexpr uint32_t OFF_STG1 = OFF_FFT;
constexpr uint32_t OFF_XCH = OFF_FFT;
constexpr uint32_t OFF_STG2 = OFF_FFT + 36864;
constexpr uint32_t OFF_BAR = 231936;
constexpr uint32_t SMEM_BYTES = OFF_BAR + 512;
constexpr uint32_t B_FULL1 = 0, B_EMPTY1 = 32, B_FULL2 = 64, B_EMPTY2 = 104, B_G1DONE = 144, B_RAW = 152, B_WST = 160, B_ADONE = 168, B_WCOL = 176, B_XCOL = 272, B_XCH = 368, B_WPK = 376, B_UST = 384, B_U2 = 432, B_U1 = 440, B_Z8 = 448;
constexpr int NB_AUX = 1, NB_EPI = 2, NB_Z = 3, NB_H = 4, NB_ALL = 5, NB_W = 6;
constexpr int C_H = 0, C_X1 = 1, C_U = 3, C_Z = 4, C_EXIT = 5, C_Z2 = 6, C_U2 = 2, C_W = 7;
#define FFT1P 2
#define PF_W1 4
#define H1 2
#define H2 3
#define WLAST 1
#define RAWW 1
#define WWAIT 3
#define UWAIT 0
#define PF0 1
#define PF0S 256
#define WHOLD 2
#define UARR 1
constexpr int NC1 = 3;

__device__ __align__(1024) uint8_t g_hT[2048 * 576 * 2];
__device__ __align__(1024) uint8_t g_U[4608 * 576 * 2];
__device__ __align__(1024) uint32_t g_x1T[289 * 2048];
__device__ __align__(1024) __nv_bfloat16 g_zT[576 * 2048];
__device__ __align__(1024) uint8_t g_T[8 * 9 * 9216];
__device__ __align__(1024) uint32_t g_wT[289 * 2048];
__device__ __align__(1024) float g_gate[2048];
__device__ __align__(1024) unsigned g_cnt[8 * 32];
#define PROF(i) do { } while (0)
#define PROFT(i) do { } while (0)

struct Params {
  const __nv_bfloat16* Ax; const __nv_bfloat16* Wr; const __nv_bfloat16* Wi;
  const __nv_bfloat16* b1; const __nv_bfloat16* b2; const __nv_bfloat16* gw; const __nv_bfloat16* W1;
};

__device__ __forceinline__ uint32_t smem_u32(const void* p) { return (uint32_t)__cvta_generic_to_shared(p); }
__device__ __forceinline__ void mbar_init(uint32_t bar, uint32_t cnt) { asm volatile("mbarrier.init.shared::cta.b64 [%0], %1;" :: "r"(bar), "r"(cnt)); }
__device__ __forceinline__ void mbar_expect_tx(uint32_t bar, uint32_t bytes) { asm volatile("mbarrier.arrive.expect_tx.shared::cta.b64 _, [%0], %1;" :: "r"(bar), "r"(bytes) : "memory"); }
__device__ __forceinline__ void mbar_arrive_cluster(uint32_t bar, uint32_t cta) {
  asm volatile("{\n.reg .b32 ra;\nmapa.shared::cluster.u32 ra, %0, %1;\nmbarrier.arrive.shared::cluster.b64 _, [ra];\n}\n" :: "r"(bar), "r"(cta) : "memory");
}
__device__ __forceinline__ void mbar_arrive(uint32_t bar) { asm volatile("mbarrier.arrive.shared::cta.b64 _, [%0];" :: "r"(bar) : "memory"); }
__device__ __forceinline__ void mbar_wait(uint32_t bar, uint32_t parity) {
  asm volatile("{\n.reg .pred p;\n.reg .u32 n;\nmov.u32 n, 0;\n"
    "LAB_WAIT:\n"
    "mbarrier.try_wait.parity.shared::cta.b64 p, [%0], %1;\n"
    "@p bra LAB_DONE;\n"
    "add.u32 n, n, 1;\n"
    "setp.lt.u32 p, n, 2000000;\n"
    "@p bra LAB_WAIT;\n"
    "trap;\n"
    "LAB_DONE:\n}\n" :: "r"(bar), "r"(parity) : "memory");
}
__device__ __forceinline__ void mbar_wait_cluster(uint32_t bar, uint32_t parity) {
  asm volatile("{\n.reg .pred p;\n.reg .u32 n;\nmov.u32 n, 0;\n"
    "LAB_WAIT:\n"
    "mbarrier.try_wait.parity.acquire.cluster.shared::cta.b64 p, [%0], %1;\n"
    "@p bra LAB_DONE;\n"
    "add.u32 n, n, 1;\n"
    "setp.lt.u32 p, n, 2000000;\n"
    "@p bra LAB_WAIT;\n"
    "trap;\n"
    "LAB_DONE:\n}\n" :: "r"(bar), "r"(parity) : "memory");
}
__device__ __forceinline__ uint32_t mapa(uint32_t addr, uint32_t cta) { uint32_t r; asm("mapa.shared::cluster.u32 %0, %1, %2;" : "=r"(r) : "r"(addr), "r"(cta)); return r; }
__device__ __forceinline__ void st_async128(uint32_t addr, float a, float b, float c, float d, uint32_t bar) {
  asm volatile("st.async.weak.shared::cluster.mbarrier::complete_tx::bytes.v4.f32 [%0], {%1,%2,%3,%4}, [%5];"
    :: "r"(addr), "f"(a), "f"(b), "f"(c), "f"(d), "r"(bar) : "memory");
}
__device__ __forceinline__ void wait_ge(const unsigned* p, unsigned target) {
  asm volatile("{\n.reg .pred p;\n.reg .u32 n, v;\nmov.u32 n, 0;\n"
    "LAB_WAIT:\n"
    "ld.acquire.gpu.global.u32 v, [%0];\n"
    "setp.ge.u32 p, v, %1;\n"
    "@p bra LAB_DONE;\n"
    "add.u32 n, n, 1;\n"
    "setp.lt.u32 p, n, 4000000;\n"
    "@p bra LAB_WAIT;\n"
    "trap;\n"
    "LAB_DONE:\n}\n" :: "l"(p), "r"(target) : "memory");
}
__device__ __forceinline__ void red_release(unsigned* p) { asm volatile("red.release.gpu.global.add.u32 [%0], 1;" :: "l"(p) : "memory"); }
__device__ __forceinline__ void red_relaxed(unsigned* p) { asm volatile("red.relaxed.gpu.global.add.u32 [%0], 1;" :: "l"(p) : "memory"); }
__device__ __forceinline__ void fence_proxy_async() { asm volatile("fence.proxy.async.global;" ::: "memory"); }
__device__ __forceinline__ void fence_proxy_async_smem() { asm volatile("fence.proxy.async.shared::cta;" ::: "memory"); }
__device__ __forceinline__ void tma_2d(uint32_t dst, const CUtensorMap* tm, int c0, int c1, uint32_t bar) {
  asm volatile("cp.async.bulk.tensor.2d.shared::cluster.global.mbarrier::complete_tx::bytes [%0], [%1, {%3, %4}], [%2];"
    :: "r"(dst), "l"(tm), "r"(bar), "r"(c0), "r"(c1) : "memory");
}
__device__ __forceinline__ void tma_2d_mc(uint32_t dst, const CUtensorMap* tm, int c0, int c1, uint32_t bar, uint16_t mask) {
  asm volatile("cp.async.bulk.tensor.2d.shared::cluster.global.mbarrier::complete_tx::bytes.multicast::cluster [%0], [%1, {%3, %4}], [%2], %5;"
    :: "r"(dst), "l"(tm), "r"(bar), "r"(c0), "r"(c1), "h"(mask) : "memory");
}
__device__ __forceinline__ void tma_prefetch_2d(const CUtensorMap* tm, int c0, int c1) {
  asm volatile("cp.async.bulk.prefetch.tensor.2d.L2.global [%0, {%1, %2}];" :: "l"(tm), "r"(c0), "r"(c1) : "memory");
}
__device__ __forceinline__ void tma_store_2d(const CUtensorMap* tm, uint32_t src, int c0, int c1) {
  asm volatile("cp.async.bulk.tensor.2d.global.shared::cta.bulk_group [%0, {%2, %3}], [%1];" :: "l"(tm), "r"(src), "r"(c0), "r"(c1) : "memory");
}
__device__ __forceinline__ void bulk_g2s(uint32_t dst, const void* src, uint32_t bytes, uint32_t bar) {
  asm volatile("cp.async.bulk.shared::cluster.global.mbarrier::complete_tx::bytes [%0], [%1], %2, [%3];"
    :: "r"(dst), "l"(src), "r"(bytes), "r"(bar) : "memory");
}
__device__ __forceinline__ void bulk_s2g(void* dst, uint32_t src, uint32_t bytes) {
  asm volatile("cp.async.bulk.global.shared::cta.bulk_group [%0], [%1], %2;" :: "l"(dst), "r"(src), "r"(bytes) : "memory");
}
__device__ __forceinline__ void bulk_s2c(uint32_t dst, uint32_t src, uint32_t bytes, uint32_t bar) {
  asm volatile("cp.async.bulk.shared::cluster.shared::cta.mbarrier::complete_tx::bytes [%0], [%1], %2, [%3];"
    :: "r"(dst), "r"(src), "r"(bytes), "r"(bar) : "memory");
}
__device__ __forceinline__ void bulk_prefetch(const void* src, uint32_t bytes) {
  asm volatile("cp.async.bulk.prefetch.L2.global [%0], %1;" :: "l"(src), "r"(bytes) : "memory");
}
__device__ __forceinline__ void prefetch_l2(const void* a) { asm volatile("prefetch.global.L2 [%0];" :: "l"(a)); }
__device__ __forceinline__ bool elect_one() {
  uint32_t pred;
  asm volatile("{\n.reg .pred P;\nelect.sync _|P, 0xffffffff;\nselp.u32 %0, 1, 0, P;\n}\n" : "=r"(pred));
  return pred;
}
__device__ __forceinline__ void wg_fence() { asm volatile("wgmma.fence.sync.aligned;" ::: "memory"); }
__device__ __forceinline__ void wg_commit() { asm volatile("wgmma.commit_group.sync.aligned;" ::: "memory"); }
template<int N> __device__ __forceinline__ void wg_wait() { asm volatile("wgmma.wait_group.sync.aligned %0;" :: "n"(N) : "memory"); }
template<int R> __device__ __forceinline__ void reg_inc() { asm volatile("setmaxnreg.inc.sync.aligned.u32 %0;" :: "n"(R)); }
template<int R> __device__ __forceinline__ void reg_dec() { asm volatile("setmaxnreg.dec.sync.aligned.u32 %0;" :: "n"(R)); }
__device__ __forceinline__ uint64_t make_desc(uint32_t addr, uint32_t lbo, uint32_t sbo, uint32_t mode) {
  return (uint64_t)((addr & 0x3FFFF) >> 4) | ((uint64_t)(lbo >> 4) << 16) | ((uint64_t)(sbo >> 4) << 32) | ((uint64_t)mode << 62);
}
__device__ __forceinline__ void cluster_arrive() { asm volatile("barrier.cluster.arrive.relaxed.aligned;" ::: "memory"); }
__device__ __forceinline__ void cluster_wait() { asm volatile("barrier.cluster.wait.aligned;" ::: "memory"); }
__device__ __forceinline__ void bar_sync(int id, int n) { asm volatile("bar.sync %0, %1;" :: "r"(id), "r"(n) : "memory"); }
__device__ __forceinline__ void bar_arrive(int id, int n) { asm volatile("bar.arrive %0, %1;" :: "r"(id), "r"(n) : "memory"); }
__device__ __forceinline__ uint32_t pack_bf16(float lo, float hi) {
  uint32_t r; asm("cvt.rn.bf16x2.f32 %0, %1, %2;" : "=r"(r) : "f"(hi), "f"(lo)); return r;
}
__device__ __forceinline__ float bf_lo(uint32_t v) { return __uint_as_float(v << 16); }
__device__ __forceinline__ float bf_hi(uint32_t v) { return __uint_as_float(v & 0xffff0000u); }
__device__ __forceinline__ float bf_round(float x) { return __bfloat162float(__float2bfloat16_rn(x)); }
__device__ __forceinline__ uint32_t badd2(uint32_t a, uint32_t b) { uint32_t r; asm("add.rn.bf16x2 %0, %1, %2;" : "=r"(r) : "r"(a), "r"(b)); return r; }
__device__ __forceinline__ uint32_t bsub2(uint32_t a, uint32_t b) { uint32_t r; asm("sub.rn.bf16x2 %0, %1, %2;" : "=r"(r) : "r"(a), "r"(b)); return r; }
__device__ __forceinline__ uint32_t bmul2(uint32_t a, uint32_t b) { uint32_t r; asm("mul.rn.bf16x2 %0, %1, %2;" : "=r"(r) : "r"(a), "r"(b)); return r; }
__device__ __forceinline__ uint4 ldg128(const void* p) { uint4 v; asm volatile("ld.global.nc.L1::no_allocate.v4.u32 {%0,%1,%2,%3}, [%4];" : "=r"(v.x), "=r"(v.y), "=r"(v.z), "=r"(v.w) : "l"(p)); return v; }
__device__ __forceinline__ uint32_t ldg16(const void* p) { uint16_t v; asm volatile("ld.global.nc.u16 %0, [%1];" : "=h"(v) : "l"(p)); return v; }
__device__ __forceinline__ void stg128(void* p, uint32_t a, uint32_t b, uint32_t c, uint32_t d) { asm volatile("st.global.v4.u32 [%0], {%1,%2,%3,%4};" :: "l"(p), "r"(a), "r"(b), "r"(c), "r"(d) : "memory"); }
__device__ __forceinline__ void stg64(void* p, uint32_t a, uint32_t b) { asm volatile("st.global.v2.u32 [%0], {%1,%2};" :: "l"(p), "r"(a), "r"(b) : "memory"); }
__device__ __forceinline__ void stg32(void* p, uint32_t a) { asm volatile("st.global.u32 [%0], %1;" :: "l"(p), "r"(a) : "memory"); }
__device__ __forceinline__ uint4 lds128(uint32_t a) { uint4 v; asm volatile("ld.shared.v4.u32 {%0,%1,%2,%3}, [%4];" : "=r"(v.x), "=r"(v.y), "=r"(v.z), "=r"(v.w) : "r"(a) : "memory"); return v; }
__device__ __forceinline__ float2 ldcg64(const float* p) { float2 v; asm volatile("ld.global.cg.v2.f32 {%0,%1}, [%2];" : "=f"(v.x), "=f"(v.y) : "l"(p) : "memory"); return v; }
__device__ __forceinline__ float4 ldcg128(const float4* p) { float4 v; asm volatile("ld.global.cg.v4.f32 {%0,%1,%2,%3}, [%4];" : "=f"(v.x), "=f"(v.y), "=f"(v.z), "=f"(v.w) : "l"(p) : "memory"); return v; }
__device__ __forceinline__ float tanh_fast(float x) { float r; asm("tanh.approx.f32 %0, %1;" : "=f"(r) : "f"(x)); return r; }
__device__ __forceinline__ float gelu_arg(float hu) {
  const float k0 = 2.0f * 0.7978845608028654f, k01 = 8.0f * 0.7978845608028654f * 0.044715f;
  return hu * fmaf(hu * hu, k01, k0);
}
__device__ __forceinline__ uint32_t bfma2(uint32_t a, uint32_t b, uint32_t c) { uint32_t r; asm("fma.rn.bf16x2 %0, %1, %2, %3;" : "=r"(r) : "r"(a), "r"(b), "r"(c)); return r; }
__device__ __forceinline__ void sts128(uint32_t a, uint32_t x, uint32_t y, uint32_t z, uint32_t w) { asm volatile("st.shared.v4.u32 [%0], {%1,%2,%3,%4};" :: "r"(a), "r"(x), "r"(y), "r"(z), "r"(w) : "memory"); }
__device__ __forceinline__ void stsm_x4(uint32_t addr, uint32_t r0, uint32_t r1, uint32_t r2, uint32_t r3) {
  asm volatile("stmatrix.sync.aligned.m8n8.x4.shared.b16 [%0], {%1,%2,%3,%4};" :: "r"(addr), "r"(r0), "r"(r1), "r"(r2), "r"(r3) : "memory");
}
__device__ __forceinline__ void stsm_x4_p(uint32_t addr, uint32_t r0, uint32_t r1, uint32_t r2, uint32_t r3, uint32_t live) {
  asm volatile("{\n.reg .pred p;\nsetp.ne.u32 p, %5, 0;\n@p stmatrix.sync.aligned.m8n8.x4.shared.b16 [%0], {%1,%2,%3,%4};\n}\n" :: "r"(addr), "r"(r0), "r"(r1), "r"(r2), "r"(r3), "r"(live) : "memory");
}
__device__ __forceinline__ void mbar_arrive_p(uint32_t bar, uint32_t live) {
  asm volatile("{\n.reg .pred p;\nsetp.ne.u32 p, %1, 0;\n@p mbarrier.arrive.shared::cta.b64 _, [%0];\n}\n" :: "r"(bar), "r"(live) : "memory");
}
__device__ __forceinline__ void stsm_x2(uint32_t addr, uint32_t r0, uint32_t r1) {
  asm volatile("stmatrix.sync.aligned.m8n8.x2.shared.b16 [%0], {%1,%2};" :: "r"(addr), "r"(r0), "r"(r1) : "memory");
}

__device__ __forceinline__ void wgmma_n72(float (&d)[36], uint64_t da, uint64_t db, int sd) {
  asm volatile("{\n.reg .pred p;\nsetp.ne.b32 p, %38, 0;\n"
    "wgmma.mma_async.sync.aligned.m64n72k16.f32.bf16.bf16 {%0, %1, %2, %3, %4, %5, %6, %7, %8, %9, %10, %11, %12, %13, %14, %15, %16, %17, %18, %19, %20, %21, %22, %23, %24, %25, %26, %27, %28, %29, %30, %31, %32, %33, %34, %35}, %36, %37, p, 1, 1, 1, 1;\n}\n"
    : "+f"(d[0]), "+f"(d[1]), "+f"(d[2]), "+f"(d[3]), "+f"(d[4]), "+f"(d[5]), "+f"(d[6]), "+f"(d[7]), "+f"(d[8]), "+f"(d[9]), "+f"(d[10]), "+f"(d[11]), "+f"(d[12]), "+f"(d[13]), "+f"(d[14]), "+f"(d[15]), "+f"(d[16]), "+f"(d[17]), "+f"(d[18]), "+f"(d[19]), "+f"(d[20]), "+f"(d[21]), "+f"(d[22]), "+f"(d[23]), "+f"(d[24]), "+f"(d[25]), "+f"(d[26]), "+f"(d[27]), "+f"(d[28]), "+f"(d[29]), "+f"(d[30]), "+f"(d[31]), "+f"(d[32]), "+f"(d[33]), "+f"(d[34]), "+f"(d[35])
    : "l"(da), "l"(db), "r"(sd));
}
__device__ __forceinline__ void wgmma_n144(float (&d)[72], uint64_t da, uint64_t db, int sd) {
  asm volatile("{\n.reg .pred p;\nsetp.ne.b32 p, %74, 0;\n"
    "wgmma.mma_async.sync.aligned.m64n144k16.f32.bf16.bf16 {%0, %1, %2, %3, %4, %5, %6, %7, %8, %9, %10, %11, %12, %13, %14, %15, %16, %17, %18, %19, %20, %21, %22, %23, %24, %25, %26, %27, %28, %29, %30, %31, %32, %33, %34, %35, %36, %37, %38, %39, %40, %41, %42, %43, %44, %45, %46, %47, %48, %49, %50, %51, %52, %53, %54, %55, %56, %57, %58, %59, %60, %61, %62, %63, %64, %65, %66, %67, %68, %69, %70, %71}, %72, %73, p, 1, 1, 1, 1;\n}\n"
    : "+f"(d[0]), "+f"(d[1]), "+f"(d[2]), "+f"(d[3]), "+f"(d[4]), "+f"(d[5]), "+f"(d[6]), "+f"(d[7]), "+f"(d[8]), "+f"(d[9]), "+f"(d[10]), "+f"(d[11]), "+f"(d[12]), "+f"(d[13]), "+f"(d[14]), "+f"(d[15]), "+f"(d[16]), "+f"(d[17]), "+f"(d[18]), "+f"(d[19]), "+f"(d[20]), "+f"(d[21]), "+f"(d[22]), "+f"(d[23]), "+f"(d[24]), "+f"(d[25]), "+f"(d[26]), "+f"(d[27]), "+f"(d[28]), "+f"(d[29]), "+f"(d[30]), "+f"(d[31]), "+f"(d[32]), "+f"(d[33]), "+f"(d[34]), "+f"(d[35]), "+f"(d[36]), "+f"(d[37]), "+f"(d[38]), "+f"(d[39]), "+f"(d[40]), "+f"(d[41]), "+f"(d[42]), "+f"(d[43]), "+f"(d[44]), "+f"(d[45]), "+f"(d[46]), "+f"(d[47]), "+f"(d[48]), "+f"(d[49]), "+f"(d[50]), "+f"(d[51]), "+f"(d[52]), "+f"(d[53]), "+f"(d[54]), "+f"(d[55]), "+f"(d[56]), "+f"(d[57]), "+f"(d[58]), "+f"(d[59]), "+f"(d[60]), "+f"(d[61]), "+f"(d[62]), "+f"(d[63]), "+f"(d[64]), "+f"(d[65]), "+f"(d[66]), "+f"(d[67]), "+f"(d[68]), "+f"(d[69]), "+f"(d[70]), "+f"(d[71])
    : "l"(da), "l"(db), "r"(sd));
}
__device__ __forceinline__ void wgmma_n192(float (&d)[96], uint64_t da, uint64_t db, int sd) {
  asm volatile("{\n.reg .pred p;\nsetp.ne.b32 p, %98, 0;\n"
    "wgmma.mma_async.sync.aligned.m64n192k16.f32.bf16.bf16 {%0, %1, %2, %3, %4, %5, %6, %7, %8, %9, %10, %11, %12, %13, %14, %15, %16, %17, %18, %19, %20, %21, %22, %23, %24, %25, %26, %27, %28, %29, %30, %31, %32, %33, %34, %35, %36, %37, %38, %39, %40, %41, %42, %43, %44, %45, %46, %47, %48, %49, %50, %51, %52, %53, %54, %55, %56, %57, %58, %59, %60, %61, %62, %63, %64, %65, %66, %67, %68, %69, %70, %71, %72, %73, %74, %75, %76, %77, %78, %79, %80, %81, %82, %83, %84, %85, %86, %87, %88, %89, %90, %91, %92, %93, %94, %95}, %96, %97, p, 1, 1, 1, 1;\n}\n"
    : "+f"(d[0]), "+f"(d[1]), "+f"(d[2]), "+f"(d[3]), "+f"(d[4]), "+f"(d[5]), "+f"(d[6]), "+f"(d[7]), "+f"(d[8]), "+f"(d[9]), "+f"(d[10]), "+f"(d[11]), "+f"(d[12]), "+f"(d[13]), "+f"(d[14]), "+f"(d[15]), "+f"(d[16]), "+f"(d[17]), "+f"(d[18]), "+f"(d[19]), "+f"(d[20]), "+f"(d[21]), "+f"(d[22]), "+f"(d[23]), "+f"(d[24]), "+f"(d[25]), "+f"(d[26]), "+f"(d[27]), "+f"(d[28]), "+f"(d[29]), "+f"(d[30]), "+f"(d[31]), "+f"(d[32]), "+f"(d[33]), "+f"(d[34]), "+f"(d[35]), "+f"(d[36]), "+f"(d[37]), "+f"(d[38]), "+f"(d[39]), "+f"(d[40]), "+f"(d[41]), "+f"(d[42]), "+f"(d[43]), "+f"(d[44]), "+f"(d[45]), "+f"(d[46]), "+f"(d[47]), "+f"(d[48]), "+f"(d[49]), "+f"(d[50]), "+f"(d[51]), "+f"(d[52]), "+f"(d[53]), "+f"(d[54]), "+f"(d[55]), "+f"(d[56]), "+f"(d[57]), "+f"(d[58]), "+f"(d[59]), "+f"(d[60]), "+f"(d[61]), "+f"(d[62]), "+f"(d[63]), "+f"(d[64]), "+f"(d[65]), "+f"(d[66]), "+f"(d[67]), "+f"(d[68]), "+f"(d[69]), "+f"(d[70]), "+f"(d[71]), "+f"(d[72]), "+f"(d[73]), "+f"(d[74]), "+f"(d[75]), "+f"(d[76]), "+f"(d[77]), "+f"(d[78]), "+f"(d[79]), "+f"(d[80]), "+f"(d[81]), "+f"(d[82]), "+f"(d[83]), "+f"(d[84]), "+f"(d[85]), "+f"(d[86]), "+f"(d[87]), "+f"(d[88]), "+f"(d[89]), "+f"(d[90]), "+f"(d[91]), "+f"(d[92]), "+f"(d[93]), "+f"(d[94]), "+f"(d[95])
    : "l"(da), "l"(db), "r"(sd));
}

__device__ __forceinline__ void fft24(float (&re)[24], float (&im)[24]) {
  const float t0 = re[0] + re[12];
  const float t1 = im[0] + im[12];
  const float t2 = re[0] - re[12];
  const float t3 = im[0] - im[12];
  const float t4 = re[6] + re[18];
  const float t5 = im[6] + im[18];
  const float t6 = re[6] - re[18];
  const float t7 = im[6] - im[18];
  const float t8 = t0 + t4;
  const float t9 = t1 + t5;
  const float t10 = t0 - t4;
  const float t11 = t1 - t5;
  const float t12 = t2 + t7;
  const float t13 = t3 - t6;
  const float t14 = t2 - t7;
  const float t15 = t3 + t6;
  const float t16 = re[3] + re[15];
  const float t17 = im[3] + im[15];
  const float t18 = re[3] - re[15];
  const float t19 = im[3] - im[15];
  const float t20 = re[9] + re[21];
  const float t21 = im[9] + im[21];
  const float t22 = re[9] - re[21];
  const float t23 = im[9] - im[21];
  const float t24 = t16 + t20;
  const float t25 = t17 + t21;
  const float t26 = t16 - t20;
  const float t27 = t17 - t21;
  const float t28 = t8 + t24;
  const float t29 = t9 + t25;
  const float t30 = t8 - t24;
  const float t31 = t9 - t25;
  const float t32 = t10 + t27;
  const float t33 = t11 - t26;
  const float t34 = t10 - t27;
  const float t35 = t11 + t26;
  const float t36 = t18 + t19;
  const float t37 = t19 - t18;
  const float t38 = t23 - t22;
  const float t39 = t23 + t22;
  const float t40 = t36 + t38;
  const float t41 = t37 - t39;
  const float t42 = t36 - t38;
  const float t43 = t37 + t39;
  const float t44 = fmaf(7.071067691e-01f, t40, t12);
  const float t45 = fmaf(7.071067691e-01f, t41, t13);
  const float t46 = fmaf(-7.071067691e-01f, t40, t12);
  const float t47 = fmaf(-7.071067691e-01f, t41, t13);
  const float t48 = fmaf(7.071067691e-01f, t43, t14);
  const float t49 = fmaf(-7.071067691e-01f, t42, t15);
  const float t50 = fmaf(-7.071067691e-01f, t43, t14);
  const float t51 = fmaf(7.071067691e-01f, t42, t15);
  const float t52 = re[8] + re[20];
  const float t53 = im[8] + im[20];
  const float t54 = re[8] - re[20];
  const float t55 = im[8] - im[20];
  const float t56 = re[14] + re[2];
  const float t57 = im[14] + im[2];
  const float t58 = re[14] - re[2];
  const float t59 = im[14] - im[2];
  const float t60 = t52 + t56;
  const float t61 = t53 + t57;
  const float t62 = t52 - t56;
  const float t63 = t53 - t57;
  const float t64 = t54 + t59;
  const float t65 = t55 - t58;
  const float t66 = t54 - t59;
  const float t67 = t55 + t58;
  const float t68 = re[11] + re[23];
  const float t69 = im[11] + im[23];
  const float t70 = re[11] - re[23];
  const float t71 = im[11] - im[23];
  const float t72 = re[17] + re[5];
  const float t73 = im[17] + im[5];
  const float t74 = re[17] - re[5];
  const float t75 = im[17] - im[5];
  const float t76 = t68 + t72;
  const float t77 = t69 + t73;
  const float t78 = t68 - t72;
  const float t79 = t69 - t73;
  const float t80 = t60 + t76;
  const float t81 = t61 + t77;
  const float t82 = t60 - t76;
  const float t83 = t61 - t77;
  const float t84 = t62 + t79;
  const float t85 = t63 - t78;
  const float t86 = t62 - t79;
  const float t87 = t63 + t78;
  const float t88 = t70 + t71;
  const float t89 = t71 - t70;
  const float t90 = t75 - t74;
  const float t91 = t75 + t74;
  const float t92 = t88 + t90;
  const float t93 = t89 - t91;
  const float t94 = t88 - t90;
  const float t95 = t89 + t91;
  const float t96 = fmaf(7.071067691e-01f, t92, t64);
  const float t97 = fmaf(7.071067691e-01f, t93, t65);
  const float t98 = fmaf(-7.071067691e-01f, t92, t64);
  const float t99 = fmaf(-7.071067691e-01f, t93, t65);
  const float t100 = fmaf(7.071067691e-01f, t95, t66);
  const float t101 = fmaf(-7.071067691e-01f, t94, t67);
  const float t102 = fmaf(-7.071067691e-01f, t95, t66);
  const float t103 = fmaf(7.071067691e-01f, t94, t67);
  const float t104 = re[16] + re[4];
  const float t105 = im[16] + im[4];
  const float t106 = re[16] - re[4];
  const float t107 = im[16] - im[4];
  const float t108 = re[22] + re[10];
  const float t109 = im[22] + im[10];
  const float t110 = re[22] - re[10];
  const float t111 = im[22] - im[10];
  const float t112 = t104 + t108;
  const float t113 = t105 + t109;
  const float t114 = t104 - t108;
  const float t115 = t105 - t109;
  const float t116 = t106 + t111;
  const float t117 = t107 - t110;
  const float t118 = t106 - t111;
  const float t119 = t107 + t110;
  const float t120 = re[19] + re[7];
  const float t121 = im[19] + im[7];
  const float t122 = re[19] - re[7];
  const float t123 = im[19] - im[7];
  const float t124 = re[1] + re[13];
  const float t125 = im[1] + im[13];
  const float t126 = re[1] - re[13];
  const float t127 = im[1] - im[13];
  const float t128 = t120 + t124;
  const float t129 = t121 + t125;
  const float t130 = t120 - t124;
  const float t131 = t121 - t125;
  const float t132 = t112 + t128;
  const float t133 = t113 + t129;
  const float t134 = t112 - t128;
  const float t135 = t113 - t129;
  const float t136 = t114 + t131;
  const float t137 = t115 - t130;
  const float t138 = t114 - t131;
  const float t139 = t115 + t130;
  const float t140 = t122 + t123;
  const float t141 = t123 - t122;
  const float t142 = t127 - t126;
  const float t143 = t127 + t126;
  const float t144 = t140 + t142;
  const float t145 = t141 - t143;
  const float t146 = t140 - t142;
  const float t147 = t141 + t143;
  const float t148 = fmaf(7.071067691e-01f, t144, t116);
  const float t149 = fmaf(7.071067691e-01f, t145, t117);
  const float t150 = fmaf(-7.071067691e-01f, t144, t116);
  const float t151 = fmaf(-7.071067691e-01f, t145, t117);
  const float t152 = fmaf(7.071067691e-01f, t147, t118);
  const float t153 = fmaf(-7.071067691e-01f, t146, t119);
  const float t154 = fmaf(-7.071067691e-01f, t147, t118);
  const float t155 = fmaf(7.071067691e-01f, t146, t119);
  const float t156 = t80 + t132;
  const float t157 = t81 + t133;
  const float t158 = t80 - t132;
  const float t159 = t81 - t133;
  const float t160 = t28 + t156;
  const float t161 = t29 + t157;
  const float t162 = fmaf(-5.000000000e-01f, t156, t28);
  const float t163 = fmaf(-5.000000000e-01f, t157, t29);
  const float t164 = fmaf(8.660253882e-01f, t159, t162);
  const float t165 = fmaf(-8.660253882e-01f, t158, t163);
  const float t166 = fmaf(-8.660253882e-01f, t159, t162);
  const float t167 = fmaf(8.660253882e-01f, t158, t163);
  const float t168 = t96 + t148;
  const float t169 = t97 + t149;
  const float t170 = t96 - t148;
  const float t171 = t97 - t149;
  const float t172 = t44 + t168;
  const float t173 = t45 + t169;
  const float t174 = fmaf(-5.000000000e-01f, t168, t44);
  const float t175 = fmaf(-5.000000000e-01f, t169, t45);
  const float t176 = fmaf(8.660253882e-01f, t171, t174);
  const float t177 = fmaf(-8.660253882e-01f, t170, t175);
  const float t178 = fmaf(-8.660253882e-01f, t171, t174);
  const float t179 = fmaf(8.660253882e-01f, t170, t175);
  const float t180 = t84 + t136;
  const float t181 = t85 + t137;
  const float t182 = t84 - t136;
  const float t183 = t85 - t137;
  const float t184 = t32 + t180;
  const float t185 = t33 + t181;
  const float t186 = fmaf(-5.000000000e-01f, t180, t32);
  const float t187 = fmaf(-5.000000000e-01f, t181, t33);
  const float t188 = fmaf(8.660253882e-01f, t183, t186);
  const float t189 = fmaf(-8.660253882e-01f, t182, t187);
  const float t190 = fmaf(-8.660253882e-01f, t183, t186);
  const float t191 = fmaf(8.660253882e-01f, t182, t187);
  const float t192 = t100 + t152;
  const float t193 = t101 + t153;
  const float t194 = t100 - t152;
  const float t195 = t101 - t153;
  const float t196 = t48 + t192;
  const float t197 = t49 + t193;
  const float t198 = fmaf(-5.000000000e-01f, t192, t48);
  const float t199 = fmaf(-5.000000000e-01f, t193, t49);
  const float t200 = fmaf(8.660253882e-01f, t195, t198);
  const float t201 = fmaf(-8.660253882e-01f, t194, t199);
  const float t202 = fmaf(-8.660253882e-01f, t195, t198);
  const float t203 = fmaf(8.660253882e-01f, t194, t199);
  const float t204 = t82 + t134;
  const float t205 = t83 + t135;
  const float t206 = t82 - t134;
  const float t207 = t83 - t135;
  const float t208 = t30 + t204;
  const float t209 = t31 + t205;
  const float t210 = fmaf(-5.000000000e-01f, t204, t30);
  const float t211 = fmaf(-5.000000000e-01f, t205, t31);
  const float t212 = fmaf(8.660253882e-01f, t207, t210);
  const float t213 = fmaf(-8.660253882e-01f, t206, t211);
  const float t214 = fmaf(-8.660253882e-01f, t207, t210);
  const float t215 = fmaf(8.660253882e-01f, t206, t211);
  const float t216 = t98 + t150;
  const float t217 = t99 + t151;
  const float t218 = t98 - t150;
  const float t219 = t99 - t151;
  const float t220 = t46 + t216;
  const float t221 = t47 + t217;
  const float t222 = fmaf(-5.000000000e-01f, t216, t46);
  const float t223 = fmaf(-5.000000000e-01f, t217, t47);
  const float t224 = fmaf(8.660253882e-01f, t219, t222);
  const float t225 = fmaf(-8.660253882e-01f, t218, t223);
  const float t226 = fmaf(-8.660253882e-01f, t219, t222);
  const float t227 = fmaf(8.660253882e-01f, t218, t223);
  const float t228 = t86 + t138;
  const float t229 = t87 + t139;
  const float t230 = t86 - t138;
  const float t231 = t87 - t139;
  const float t232 = t34 + t228;
  const float t233 = t35 + t229;
  const float t234 = fmaf(-5.000000000e-01f, t228, t34);
  const float t235 = fmaf(-5.000000000e-01f, t229, t35);
  const float t236 = fmaf(8.660253882e-01f, t231, t234);
  const float t237 = fmaf(-8.660253882e-01f, t230, t235);
  const float t238 = fmaf(-8.660253882e-01f, t231, t234);
  const float t239 = fmaf(8.660253882e-01f, t230, t235);
  const float t240 = t102 + t154;
  const float t241 = t103 + t155;
  const float t242 = t102 - t154;
  const float t243 = t103 - t155;
  const float t244 = t50 + t240;
  const float t245 = t51 + t241;
  const float t246 = fmaf(-5.000000000e-01f, t240, t50);
  const float t247 = fmaf(-5.000000000e-01f, t241, t51);
  const float t248 = fmaf(8.660253882e-01f, t243, t246);
  const float t249 = fmaf(-8.660253882e-01f, t242, t247);
  const float t250 = fmaf(-8.660253882e-01f, t243, t246);
  const float t251 = fmaf(8.660253882e-01f, t242, t247);
  re[0] = t160;
  im[0] = t161;
  re[1] = t176;
  im[1] = t177;
  re[2] = t190;
  im[2] = t191;
  re[3] = t196;
  im[3] = t197;
  re[4] = t212;
  im[4] = t213;
  re[5] = t226;
  im[5] = t227;
  re[6] = t232;
  im[6] = t233;
  re[7] = t248;
  im[7] = t249;
  re[8] = t166;
  im[8] = t167;
  re[9] = t172;
  im[9] = t173;
  re[10] = t188;
  im[10] = t189;
  re[11] = t202;
  im[11] = t203;
  re[12] = t208;
  im[12] = t209;
  re[13] = t224;
  im[13] = t225;
  re[14] = t238;
  im[14] = t239;
  re[15] = t244;
  im[15] = t245;
  re[16] = t164;
  im[16] = t165;
  re[17] = t178;
  im[17] = t179;
  re[18] = t184;
  im[18] = t185;
  re[19] = t200;
  im[19] = t201;
  re[20] = t214;
  im[20] = t215;
  re[21] = t220;
  im[21] = t221;
  re[22] = t236;
  im[22] = t237;
  re[23] = t250;
  im[23] = t251;
}

__device__ __forceinline__ void fft8(float (&re)[8], float (&im)[8]) {
  const float t0 = re[0] + re[4];
  const float t1 = im[0] + im[4];
  const float t2 = re[0] - re[4];
  const float t3 = im[0] - im[4];
  const float t4 = re[2] + re[6];
  const float t5 = im[2] + im[6];
  const float t6 = re[2] - re[6];
  const float t7 = im[2] - im[6];
  const float t8 = t0 + t4;
  const float t9 = t1 + t5;
  const float t10 = t0 - t4;
  const float t11 = t1 - t5;
  const float t12 = t2 + t7;
  const float t13 = t3 - t6;
  const float t14 = t2 - t7;
  const float t15 = t3 + t6;
  const float t16 = re[1] + re[5];
  const float t17 = im[1] + im[5];
  const float t18 = re[1] - re[5];
  const float t19 = im[1] - im[5];
  const float t20 = re[3] + re[7];
  const float t21 = im[3] + im[7];
  const float t22 = re[3] - re[7];
  const float t23 = im[3] - im[7];
  const float t24 = t16 + t20;
  const float t25 = t17 + t21;
  const float t26 = t16 - t20;
  const float t27 = t17 - t21;
  const float t28 = t8 + t24;
  const float t29 = t9 + t25;
  const float t30 = t8 - t24;
  const float t31 = t9 - t25;
  const float t32 = t10 + t27;
  const float t33 = t11 - t26;
  const float t34 = t10 - t27;
  const float t35 = t11 + t26;
  const float t36 = t18 + t19;
  const float t37 = t19 - t18;
  const float t38 = t23 - t22;
  const float t39 = t23 + t22;
  const float t40 = t36 + t38;
  const float t41 = t37 - t39;
  const float t42 = t36 - t38;
  const float t43 = t37 + t39;
  const float t44 = fmaf(7.071067691e-01f, t40, t12);
  const float t45 = fmaf(7.071067691e-01f, t41, t13);
  const float t46 = fmaf(-7.071067691e-01f, t40, t12);
  const float t47 = fmaf(-7.071067691e-01f, t41, t13);
  const float t48 = fmaf(7.071067691e-01f, t43, t14);
  const float t49 = fmaf(-7.071067691e-01f, t42, t15);
  const float t50 = fmaf(-7.071067691e-01f, t43, t14);
  const float t51 = fmaf(7.071067691e-01f, t42, t15);
  re[0] = t28;
  im[0] = t29;
  re[1] = t44;
  im[1] = t45;
  re[2] = t32;
  im[2] = t33;
  re[3] = t48;
  im[3] = t49;
  re[4] = t30;
  im[4] = t31;
  re[5] = t46;
  im[5] = t47;
  re[6] = t34;
  im[6] = t35;
  re[7] = t50;
  im[7] = t51;
}

template<int N> __device__ __forceinline__ void fence_regs(float (&a)[N]) {
  #pragma unroll
  for (int i = 0; i < N; i++) asm volatile("" : "+f"(a[i]) :: "memory");
}

__device__ __forceinline__ const __nv_bfloat16* w_src(const Params& p, int cta, int lane) {
  const int u = cta >> 1, rr = u >> 5, g = (u >> 2) & 7, t = u & 3;
  return ((lane >> 2) ? p.Wi : p.Wr) + (size_t)(8 * (2 * g + rr) + 128 * (8 * ((lane >> 1) & 1) + 2 * t + (lane & 1)) + 4 * (cta & 1)) * 289;
}
constexpr uint32_t WSLOT = 2560;
__device__ __forceinline__ void w_stage(const Params& p, uint32_t dst, uint32_t bars, int cta, int lane) {
  const uintptr_t src = reinterpret_cast<uintptr_t>(w_src(p, cta, lane & 7));
  const uint32_t off = (uint32_t)src & 127u;
  const uint32_t len = (off + 2312 + 15) & ~15u;
  uint32_t tot = (lane < 8) ? len : 0;
  #pragma unroll
  for (int o = 1; o < 8; o <<= 1) tot += __shfl_xor_sync(0xffffffffu, tot, o);
  if (lane == 0) { fence_proxy_async_smem(); mbar_expect_tx(bars + B_WST, tot); }
  __syncwarp();
  if (lane < 8) bulk_g2s(dst + lane * WSLOT, reinterpret_cast<const void*>(src - off), len, bars + B_WST);
  __syncwarp();
}
__device__ __forceinline__ void w_pack(const Params& p, const CUtensorMap* tmWt, const uint8_t* sm, uint32_t sbase, int cta, int cw, int lane) {
  mbar_wait(sbase + OFF_BAR + B_WST, 0);
  const int r = cw & 3, c0 = (cw >> 2) * 145 + lane;
  const uint16_t* wr = reinterpret_cast<const uint16_t*>(sm + OFF_WSR + r * 578) + c0;
  uint32_t offs[8];
  #pragma unroll
  for (int i = 0; i < 8; i++) offs[i] = ((uint32_t)reinterpret_cast<uintptr_t>(w_src(p, cta, i)) & 127u) / 2 + i * (WSLOT / 2);
  const int nc = (cw >> 2) ? 144 : 145;
  uint32_t o[5][4];
  #pragma unroll
  for (int j = 0; j < 5; j++)
    #pragma unroll
    for (int he = 0; he < 4; he++)
      o[j][he] = (lane + 32 * j < nc) ? ((uint32_t)wr[offs[he] + 32 * j] | ((uint32_t)wr[offs[4 + he] + 32 * j] << 16)) : 0u;
  bar_sync(NB_W, 256);
  const uint32_t slot = ((4 * (cta & 1) + r) ^ (cta >> 1)) & 3;
  #pragma unroll
  for (int j = 0; j < 5; j++) {
    const uint32_t c = c0 + 32 * j;
    if (lane + 32 * j < nc) sts128(sbase + OFF_WSR + c * 64 + ((slot ^ (c >> 1)) & 3) * 16, o[j][0], o[j][1], o[j][2], o[j][3]);
  }
  bar_sync(NB_W, 256);
  if (cw == 0 && lane == 0) {
    const int x = 32 * (cta >> 1) + 16 * (((cta & 1) ^ (cta >> 3)) & 1);
    fence_proxy_async_smem();
    tma_store_2d(tmWt, sbase + OFF_WSR, x, 0);
    tma_store_2d(tmWt, sbase + OFF_WSR + 160 * 64, x, 160);
    asm volatile("cp.async.bulk.commit_group;" ::: "memory");
  }
}
__device__ __forceinline__ void w_publish(uint32_t sbase) {
  asm volatile("cp.async.bulk.wait_group 0;" ::: "memory");
  fence_proxy_async();
  red_relaxed(&g_cnt[C_W * 32]);
  mbar_arrive(sbase + OFF_BAR + B_WPK);
}

__device__ __forceinline__ void fft_stage_a(const CUtensorMap* tmX, uint8_t* sm, uint32_t sbase, int cta, int at) {
  const uint32_t bars = sbase + OFF_BAR;
  float2* twA = reinterpret_cast<float2*>(sm + OFF_TWA);
  #pragma unroll 1
  for (int i = at; i < 576; i += 96) {
    int k1 = i / 24, n2 = i - 24 * k1;
    float s, c; sincospif(-(float)(k1 * n2) * (1.0f / 288.0f), &s, &c);
    twA[i] = make_float2(c, s);
  }
  if (at == 0) PROF(21);
  bar_sync(NB_AUX, 96);
  mbar_wait(bars + B_RAW, 0);
  if (at == 0) PROF(22);
  const uint16_t* raw = reinterpret_cast<const uint16_t*>(sm + OFF_RAW);
  uint8_t* exch = sm + OFF_EXCH;
  const int n2 = at % 24, p1 = at / 24;
  const int q = at >> 3, pr = at & 7;
  float re[24], im[24], pr_[24], pi_[24];
  #pragma unroll 1
  for (int it = 0; it < 4; it++) {
    if (it < 2) {
      const uint16_t* ra = raw + (2 * (p1 + 4 * it)) * 576 + n2;
      #pragma unroll
      for (int n1 = 0; n1 < 24; n1++) { re[n1] = __uint_as_float((uint32_t)ra[24 * n1] << 16); im[n1] = __uint_as_float((uint32_t)ra[576 + 24 * n1] << 16); }
    } else {
      if (it == 2) { if (at == 0) PROF(23); bar_sync(NB_AUX, 96); }
      const int k1 = (it == 2) ? q : (q ? 24 - q : 12);
      const float4* row = reinterpret_cast<const float4*>(exch + pr * 4624 + k1 * 192);
      #pragma unroll
      for (int i = 0; i < 12; i++) { float4 v = row[i]; re[2*i] = v.x; im[2*i] = v.y; re[2*i+1] = v.z; im[2*i+1] = v.w; }
    }
    fft24(re, im);
    if (it < 2) {
      float2* ex = reinterpret_cast<float2*>(exch + (p1 + 4 * it) * 4624) + n2;
      #pragma unroll
      for (int k1 = 1; k1 < 24; k1++) {
        const float2 w = twA[k1 * 24 + n2];
        const float r = re[k1], m = im[k1];
        re[k1] = r * w.x - m * w.y; im[k1] = r * w.y + m * w.x;
      }
      #pragma unroll
      for (int k1 = 0; k1 < 24; k1++) ex[k1 * 24] = make_float2(re[k1], im[k1]);
    } else if (it == 2) {
      #pragma unroll
      for (int i = 0; i < 24; i++) { pr_[i] = re[i]; pi_[i] = im[i]; }
    }
  }
  if (at == 0) PROF(24);
  bar_sync(NB_AUX, 96);
  const int n1 = cta & 15;
  {
    uint2* xs = reinterpret_cast<uint2*>(sm + OFF_XST + ((2 * pr) ^ (2 * (n1 & 4))) * 4);
    uint2* xo1 = xs + q * 8;
    uint2* xo2 = xs + (q ? 24 - q : 12) * 8;
    const bool q0 = (q == 0);
    #pragma unroll
    for (int k2 = 0; k2 < 12; k2++) {
      {
        const float mr = q0 ? pr_[(24 - k2) % 24] : re[23 - k2], mi = q0 ? pi_[(24 - k2) % 24] : im[23 - k2];
        xo1[k2 * (24 * 8)] = make_uint2(pack_bf16(pr_[k2] + mr, pi_[k2] - mi), pack_bf16(pi_[k2] + mi, mr - pr_[k2]));
      }
      {
        const float mr = q0 ? re[23 - k2] : pr_[23 - k2], mi = q0 ? im[23 - k2] : pi_[23 - k2];
        xo2[k2 * (24 * 8)] = make_uint2(pack_bf16(re[k2] + mr, im[k2] - mi), pack_bf16(im[k2] + mi, mr - re[k2]));
      }
    }
    if (q0) xs[288 * 8] = make_uint2(pack_bf16(2.0f * pr_[12], 0.0f), pack_bf16(2.0f * pi_[12], 0.0f));
  }
  if (at == 0) PROF(25);
  bar_sync(NB_AUX, 96);
  if (at == 0) {
    const int pos = 256 * (cta >> 4) + 16 * ((n1 & 12) | ((n1 & 1) << 1) | ((n1 >> 1) & 1));
    fence_proxy_async_smem();
    tma_store_2d(tmX, sbase + OFF_XST, pos, 0);
    tma_store_2d(tmX, sbase + OFF_XST + 146 * 64, pos, 146);
    asm volatile("cp.async.bulk.commit_group;" ::: "memory");
    asm volatile("cp.async.bulk.wait_group 0;" ::: "memory");
    fence_proxy_async();
    red_relaxed(&g_cnt[C_X1 * 32]);
    PROF(8);
    if (cta < 108) {
      mbar_arrive(bars + B_G1DONE);
      mbar_arrive(bars + B_ADONE);
    }
  }
  __syncwarp();
}

__device__ __forceinline__ void h_publish(uint32_t sbase, int cta, int lane) {
  bar_sync(NB_H, 288);
  fence_proxy_async_smem();
  if (lane < 3) bulk_s2g(g_hT + (size_t)lane * (32 * 24576) + cta * 6144, sbase + OFF_HST + lane * 6144, 6144);
  asm volatile("cp.async.bulk.commit_group;" ::: "memory");
  __syncwarp();
  asm volatile("cp.async.bulk.wait_group 0;" ::: "memory");
  fence_proxy_async();
  __syncwarp();
  if (lane == 0) red_relaxed(&g_cnt[C_H * 32]);
  if (lane == 0) PROF(20);
  __syncwarp();
}
__device__ __forceinline__ void t_gen(uint8_t* sm, int f, int tid) {
  float* ctab = reinterpret_cast<float*>(sm + OFF_CTAB);
  #pragma unroll 1
  for (int i = tid; i < 576; i += 384) ctab[i] = __cosf((float)(i < 288 ? i : i - 576) * (3.14159265358979f / 288.0f));
  bar_sync(NB_ALL, 384);
  const int sl0 = tid / 72, rem = tid - 72 * sl0, r = rem & 7, ng = rem >> 3;
  #pragma unroll 1
  for (int sl = sl0; sl < 18 && tid < 360; sl += 5) {
    const int slab = 18 * f + sl;
    const int tile = slab / 9, kb = slab - 9 * tile;
    const int d0 = (tile >> 1) * 144 + (tile & 1) * 72 + 8 * ng;
    uint8_t* out = g_T + (size_t)slab * 9216 + rem * 16;
    #pragma unroll 2
    for (int kg = 0; kg < 8; kg++) {
      const int j = 64 * kb + 8 * kg + r;
      const uint32_t k = (j < 574) ? (j >> 1) + 1 : (j == 574 ? 0 : 288);
      const float sc = (j < 574) ? 2.0f : 1.0f;
      const uint32_t ix = (k * d0 + ((j < 574 && (j & 1)) ? 144 : 0)) % 576u;
      float v[8];
      const float m2 = 2.0f * ctab[k];
      v[0] = sc * ctab[ix]; v[1] = sc * ctab[(ix + k) % 576u];
      #pragma unroll
      for (int c = 2; c < 8; c++) v[c] = fmaf(m2, v[c-1], -v[c-2]);
      stg128(out + kg * 1152, pack_bf16(v[0], v[1]), pack_bf16(v[2], v[3]), pack_bf16(v[4], v[5]), pack_bf16(v[6], v[7]));
    }
  }
}

__device__ __forceinline__ void mma16816(float (&d)[4], uint32_t a0, uint32_t a1, uint32_t a2, uint32_t a3, uint32_t b0, uint32_t b1) {
  asm("mma.sync.aligned.m16n8k16.row.col.f32.bf16.bf16.f32 {%0,%1,%2,%3}, {%4,%5,%6,%7}, {%8,%9}, {%0,%1,%2,%3};"
      : "+f"(d[0]), "+f"(d[1]), "+f"(d[2]), "+f"(d[3]) : "r"(a0), "r"(a1), "r"(a2), "r"(a3), "r"(b0), "r"(b1));
}
__device__ __forceinline__ void mma16816_z(float (&d)[4], uint32_t a0, uint32_t a1, uint32_t a2, uint32_t a3, uint32_t b0, uint32_t b1) {
  asm("mma.sync.aligned.m16n8k16.row.col.f32.bf16.bf16.f32 {%0,%1,%2,%3}, {%4,%5,%6,%7}, {%8,%9}, {%10,%10,%10,%10};"
      : "=f"(d[0]), "=f"(d[1]), "=f"(d[2]), "=f"(d[3]) : "r"(a0), "r"(a1), "r"(a2), "r"(a3), "r"(b0), "r"(b1), "f"(0.0f));
}
__device__ __forceinline__ void cis2048(int e, float& c, float& s) {
  e = ((e + 1024) & 2047) - 1024;
  const float x = (float)e * (3.14159265358979f / 1024.0f);
  c = __cosf(x); s = __sinf(x);
}
__device__ __forceinline__ void tcfft_tab_init(uint8_t* tab, int at) {
  #pragma unroll 1
  for (int i = at; i < 512; i += 256) {
    const int r = i & 3, lane = (i >> 2) & 31, st = i >> 7;
    const int g = lane >> 2, t = lane & 3;
    float c[2], s[2], dc[2], ds[2];
    #pragma unroll
    for (int u = 0; u < 2; u++) {
      int de, m;
      if (st == 0) { de = -16 * (2 * t + 8 * (r >> 1) + u); m = 8 * (2 * g + (r & 1)); }
      else if (st == 1) { de = -(4 * t + 2 * u + (r & 1)); m = 128 * (8 * (r >> 1) + g); }
      else if (st == 2) { de = 2 * g + (r & 1); m = 128 * (2 * t + 8 * (r >> 1) + u); }
      else { de = 16 * (g + 8 * (r & 1)); m = 8 * (4 * t + 2 * u + (r >> 1)); }
      cis2048(de * m, c[u], s[u]); cis2048(de, dc[u], ds[u]);
    }
    uint32_t* o = reinterpret_cast<uint32_t*>(tab + st * 8192) + lane * 4 + r;
    #pragma unroll 1
    for (int ka = 0; ka < 8; ka++) {
      o[ka * 256] = pack_bf16(c[0], c[1]); o[ka * 256 + 128] = pack_bf16(s[0], s[1]);
      #pragma unroll
      for (int u = 0; u < 2; u++) { const float cn = c[u] * dc[u] - s[u] * ds[u]; s[u] = c[u] * ds[u] + s[u] * dc[u]; c[u] = cn; }
    }
  }
  {
    const int u = at & 1, lane = (at >> 1) & 31, q = at >> 6, ps = 2 * q + u, h = ps >> 2, d = ps & 3;
    const int g = lane >> 2, t = lane & 3;
    float s, c; cis2048(-8 * (2 * g + (d >> 1)) * (4 * t + 2 * (d & 1) + h), c, s);
    reinterpret_cast<float2*>(tab + 32768)[at] = make_float2(c, s);
  }
}
__device__ __forceinline__ void cmma_a(uint32_t tp, const uint32_t (&br)[4], const uint32_t (&bi)[4], float (&dr)[2][4], float (&di)[2][4]) {
  const uint4 cr = lds128(tp), ci = lds128(tp + 512);
  const uint32_t n0 = ci.x ^ 0x80008000u, n1 = ci.y ^ 0x80008000u, n2 = ci.z ^ 0x80008000u, n3 = ci.w ^ 0x80008000u;
  #pragma unroll
  for (int h = 0; h < 2; h++) {
    mma16816_z(dr[h], cr.x, cr.y, cr.z, cr.w, br[2*h], br[2*h+1]);
    mma16816_z(di[h], ci.x, ci.y, ci.z, ci.w, br[2*h], br[2*h+1]);
    mma16816(dr[h], n0, n1, n2, n3, bi[2*h], bi[2*h+1]);
    mma16816(di[h], cr.x, cr.y, cr.z, cr.w, bi[2*h], bi[2*h+1]);
  }
}
__device__ __forceinline__ void cmma_b(uint32_t tp, const uint32_t (&ar)[4], const uint32_t (&ai)[4], float (&dr)[2][4], float (&di)[2][4]) {
  const uint4 cr = lds128(tp), ci = lds128(tp + 512);
  const uint32_t r4[4] = {cr.x, cr.y, cr.z, cr.w}, i4[4] = {ci.x, ci.y, ci.z, ci.w};
  #pragma unroll
  for (int h = 0; h < 2; h++) {
    mma16816_z(dr[h], ar[0], ar[1], ar[2], ar[3], r4[2*h], r4[2*h+1]);
    mma16816_z(di[h], ar[0], ar[1], ar[2], ar[3], i4[2*h], i4[2*h+1]);
    mma16816(dr[h], ai[0], ai[1], ai[2], ai[3], i4[2*h] ^ 0x80008000u, i4[2*h+1] ^ 0x80008000u);
    mma16816(di[h], ai[0], ai[1], ai[2], ai[3], r4[2*h], r4[2*h+1]);
  }
}
__device__ __forceinline__ void tcfft_wload(uint32_t sbase, int warp, int lane, int col) {
  if (lane == 0) {
    const uint32_t bar = sbase + OFF_BAR + B_WCOL + 8 * warp;
    mbar_expect_tx(bar, 8192);
    bulk_g2s(sbase + OFF_WCOL + warp * 8192, g_wT + (size_t)col * 2048, 8192, bar);
  }
  __syncwarp();
}
#define TW_LOAD() do { _Pragma("unroll") for (int i_ = 0; i_ < 4; i_++) { const uint4 v_ = lds128(tl + 32768 + i_ * 512); \
  twr[2*i_] = __uint_as_float(v_.x); twi[2*i_] = __uint_as_float(v_.y); twr[2*i_+1] = __uint_as_float(v_.z); twi[2*i_+1] = __uint_as_float(v_.w); } } while (0)
__device__ __forceinline__ void tcfft_column(int col, uint32_t par) {
  extern __shared__ __align__(1024) uint8_t sm[];
  const uint32_t sbase = smem_u32(sm);
  const int warp = threadIdx.x >> 5, lane = threadIdx.x & 31;
  const int g = lane >> 2, t = lane & 3;
  const uint32_t bars = sbase + OFF_BAR;
  uint8_t* xs = sm + OFF_XCOL + warp * 8192;
  float re[8][8], im[8][8];
  if (lane == 0) {
    mbar_expect_tx(bars + B_XCOL + 8 * warp, 8192);
    bulk_g2s(sbase + OFF_XCOL + warp * 8192, g_x1T + (size_t)col * 2048, 8192, bars + B_XCOL + 8 * warp);
  }
  __syncwarp();
  tcfft_wload(sbase, warp, lane, col);
  #pragma unroll 1
  for (int it = 0; it < 2; it++) {
    if (it == 0) {
      mbar_wait(bars + B_XCOL + 8 * warp, par);
      const uint8_t* xp = xs + (t >> 1) * 256 + (t & 1) * 64 + ((8 * g) ^ (32 * (t >> 1)));
      #pragma unroll
      for (int n2 = 0; n2 < 8; n2++)
        #pragma unroll
        for (int j = 0; j < 4; j++) {
          const uint2 v = *reinterpret_cast<const uint2*>(xp + n2 * 1024 + (j >> 1) * 512 + (j & 1) * 128);
          re[2*j][n2] = bf_lo(v.x); im[2*j][n2] = bf_hi(v.x); re[2*j+1][n2] = bf_lo(v.y); im[2*j+1][n2] = bf_hi(v.y);
        }
    }
    if (threadIdx.x == 160) PROF(32 + 3 * it);
    #pragma unroll
    for (int ps = 0; ps < 8; ps++) fft8(re[ps], im[ps]);
    if (threadIdx.x == 160) PROF(33 + 3 * it);
    if (it == 0) {
      uint32_t pk[8][8];
      #pragma unroll
      for (int ka = 0; ka < 8; ka++)
        #pragma unroll
        for (int h = 0; h < 2; h++) {
          pk[ka][2*h]     = pack_bf16(re[0+h][ka], re[2+h][ka]);
          pk[ka][2*h+1]   = pack_bf16(re[4+h][ka], re[6+h][ka]);
          pk[ka][4+2*h]   = pack_bf16(im[0+h][ka], im[2+h][ka]);
          pk[ka][4+2*h+1] = pack_bf16(im[4+h][ka], im[6+h][ka]);
        }
      uint32_t tl = sbase + OFF_TAB + lane * 16;
      uint32_t wl = sbase + OFF_WCOL + warp * 8192 + lane * 128 + (lane & 7) * 16;
      asm volatile("" : "+r"(tl), "+r"(wl));
      float twr[8], twi[8];
      if (threadIdx.x == 160) PROF(34);
      #pragma unroll
      for (int ka = 0; ka < 8; ka++) {
        float dr[2][4], di[2][4];
        uint32_t xr[4], xi[4];
        #pragma unroll
        for (int i = 0; i < 4; i++) { xr[i] = pk[ka][i]; xi[i] = pk[ka][4 + i]; }
        cmma_a(tl + (0 * 8 + ka) * 1024, xr, xi, dr, di);
        TW_LOAD();
        #pragma unroll
        for (int h = 0; h < 2; h++)
          #pragma unroll
          for (int d = 0; d < 4; d++) {
            const float a = dr[h][d], b = di[h][d], c = twr[4*h+d], s = twi[4*h+d];
            dr[h][d] = a * c - b * s; di[h][d] = a * s + b * c;
          }
        #pragma unroll
        for (int h = 0; h < 2; h++) {
          xr[2*h] = pack_bf16(dr[h][0], dr[h][1]); xr[2*h+1] = pack_bf16(dr[h][2], dr[h][3]);
          xi[2*h] = pack_bf16(di[h][0], di[h][1]); xi[2*h+1] = pack_bf16(di[h][2], di[h][3]);
        }
        cmma_b(tl + (1 * 8 + ka) * 1024, xr, xi, dr, di);
        {
          if (ka == 0) mbar_wait(bars + B_WCOL + 8 * warp, par);
          const uint32_t wk = wl ^ (ka * 16);
          const uint4 w0 = lds128(wk), w1 = lds128(wk + 4096);
          const uint32_t wa[4] = {w0.x, w0.y, w0.z, w0.w}, wb[4] = {w1.x, w1.y, w1.z, w1.w};
          #pragma unroll
          for (int h = 0; h < 2; h++)
            #pragma unroll
            for (int d = 0; d < 4; d++) {
              const uint32_t w = (d >> 1) ? wb[2*h + (d & 1)] : wa[2*h + (d & 1)];
              const float a = dr[h][d], b = di[h][d], c = bf_lo(w), s = bf_hi(w);
              dr[h][d] = a * c - b * s; di[h][d] = a * s + b * c;
            }
        }
        #pragma unroll
        for (int hh = 0; hh < 2; hh++) {
          xr[2*hh] = pack_bf16(dr[0][2*hh], dr[0][2*hh+1]); xr[2*hh+1] = pack_bf16(dr[1][2*hh], dr[1][2*hh+1]);
          xi[2*hh] = pack_bf16(di[0][2*hh], di[0][2*hh+1]); xi[2*hh+1] = pack_bf16(di[1][2*hh], di[1][2*hh+1]);
        }
        cmma_a(tl + (2 * 8 + ka) * 1024, xr, xi, dr, di);
        TW_LOAD();
        #pragma unroll
        for (int h = 0; h < 2; h++)
          #pragma unroll
          for (int d = 0; d < 4; d++) {
            const float a = dr[h][d], b = di[h][d], c = twr[4*h+d], s = twi[4*h+d];
            dr[h][d] = a * c + b * s; di[h][d] = b * c - a * s;
          }
        #pragma unroll
        for (int hh = 0; hh < 2; hh++) {
          xr[2*hh] = pack_bf16(dr[0][2*hh], dr[0][2*hh+1]); xr[2*hh+1] = pack_bf16(dr[1][2*hh], dr[1][2*hh+1]);
          xi[2*hh] = pack_bf16(di[0][2*hh], di[0][2*hh+1]); xi[2*hh+1] = pack_bf16(di[1][2*hh], di[1][2*hh+1]);
        }
        cmma_a(tl + (3 * 8 + ka) * 1024, xr, xi, dr, di);
        #pragma unroll
        for (int h = 0; h < 2; h++)
          #pragma unroll
          for (int d = 0; d < 4; d++) { re[4*h+d][ka] = di[h][d]; im[4*h+d][ka] = dr[h][d]; }
      }
    } else {
      uint2* zr = reinterpret_cast<uint2*>(xs + 32 * g + 8 * t);
      #pragma unroll
      for (int n2 = 0; n2 < 8; n2++)
        #pragma unroll
        for (int rr = 0; rr < 2; rr++) {
          zr[n2 * 64 + rr * 32] = make_uint2(pack_bf16(im[2*rr][n2], im[4+2*rr][n2]), pack_bf16(im[2*rr+1][n2], im[4+2*rr+1][n2]));
          zr[512 + n2 * 64 + rr * 32] = make_uint2(pack_bf16(re[2*rr][n2], re[4+2*rr][n2]), pack_bf16(re[2*rr+1][n2], re[4+2*rr+1][n2]));
        }
    }
  }
  fence_proxy_async_smem();
  __syncwarp();
  const bool urgent = (col >= 1) && (col <= 32 * NC1);
  if (!urgent && par == 0) bar_sync(NB_Z, 384);
  if (lane == 0) {
    const bool cplx = (col != 0) && (col != 288);
    const int zrow = (col == 0) ? 574 : (col == 288 ? 575 : 2 * col - 2);
    bulk_s2g(g_zT + (size_t)zrow * 2048, sbase + OFF_XCOL + warp * 8192, cplx ? 8192 : 4096);
    asm volatile("cp.async.bulk.commit_group;" ::: "memory");
    asm volatile("cp.async.bulk.wait_group 0;" ::: "memory");
    fence_proxy_async();
    red_relaxed(&g_cnt[(urgent ? C_Z : C_Z2) * 32]);
  }
  __syncwarp();
  if (urgent) bar_arrive(NB_Z, 384);
}

__global__ void __launch_bounds__(384, 1)
fused_kernel(const __grid_constant__ CUtensorMap tmW1, const __grid_constant__ CUtensorMap tmW2,
             const __grid_constant__ CUtensorMap tmZ, const __grid_constant__ CUtensorMap tmOut,
             const __grid_constant__ CUtensorMap tmX, const __grid_constant__ CUtensorMap tmWt, const Params p) {
  extern __shared__ __align__(1024) uint8_t sm[];
  const uint32_t sbase = smem_u32(sm);
  const uint32_t bars = sbase + OFF_BAR;
  const int tid = threadIdx.x, warp = tid >> 5, lane = tid & 31;
  const int cta = blockIdx.x;
  const uint32_t rank = cta & 1;

  if (lane == 0) {
    if (warp == 0) {
      PROF(0); PROFT(60);
      if (sbase & 1023) __trap();
      mbar_init(bars + B_RAW, 1);
      if (cta < 128) {
        fence_proxy_async_smem();
        mbar_expect_tx(bars + B_RAW, 18432);
        bulk_g2s(sbase + OFF_RAW, p.Ax + (size_t)cta * 16 * 576, 18432, bars + B_RAW);
      }
    }
    #pragma unroll 1
    for (int b = warp; b < 57; b += 12)
      if (b != 19) mbar_init(bars + 8 * b, (b >= 4 && b < 8) ? 2 : (b >= 13 && b < 18) ? 2 : (b == 18) ? 3 : (b >= 48 && b < 54) ? 8 : 1);
    if (warp == 10) mbar_expect_tx(bars + B_XCH, 36864);
    asm volatile("fence.mbarrier_init.release.cluster;" ::: "memory");
  }
  if (PF0 && warp == 1 && cta < 128) {
    const void* a = (lane < 8) ? (const void*)w_src(p, cta, lane) : (const void*)(p.W1 + (size_t)(lane - 8) * (PF0S * 4608) + 128 * (cta / 3));
    if (lane < 8 || (lane < 8 + PF0 && cta < 108)) asm volatile("prefetch.global.L2 [%0];" :: "l"(a));
  }
  __syncthreads();
  cluster_arrive();

  if (cta >= 128) {
    t_gen(sm, cta - 128, tid);
    bar_sync(NB_ALL, 384);
    if (tid == 0) { red_release(&g_cnt[C_Z * 32]); PROF(28); }
  }

  const int cl = cta >> 1;
  int mt, nt; const int ks = (int)rank;
  {
    const int t = cl - 4;
    if (cl < 4) { mt = 15; nt = cl; }
    else {
      const int g = (t < 32) ? (t & 7) : 1 + (t - 32) % 7, r = (t < 32) ? (t >> 3) : 4 + (t - 32) / 7;
      if (g == 0) { mt = 14; nt = r; } else { mt = 2 * (g - 1) + (r >> 2); nt = r & 3; }
    }
  }
  const bool fftcta = cta >= 108;
  const int ct = tid - 128, cw = warp - 4, wg = cw >> 2, wq = cw & 3;
  uint32_t braw0 = 0, braw1 = 0;

  if (warp == 0) {
    if (cta < 128) {
      if (RAWW) mbar_wait(bars + B_RAW, 0);
      if (!WLAST) w_stage(p, sbase + OFF_WSR, bars, cta, lane);
      if (!fftcta && elect_one()) {
        const int f0 = 128 * (cta / 3);
        mbar_expect_tx(bars + B_FULL1, ST1);
        tma_2d(sbase, &tmW1, f0, 0, bars + B_FULL1);
        tma_2d(sbase + 8192, &tmW1, f0 + 64, 0, bars + B_FULL1);
        #pragma unroll 1
        for (int s = 1; s < PF_W1; s++) {
          tma_prefetch_2d(&tmW1, f0, 64 * s);
          tma_prefetch_2d(&tmW1, f0 + 64, 64 * s);
        }
      }
      __syncwarp();
      if (WLAST) w_stage(p, sbase + OFF_WSR, bars, cta, lane);
    }
    if (!fftcta) {
      const int mt1 = cta / 3, dt = cta - 3 * mt1;
      const int f0 = 128 * mt1;
      const uint8_t* Bt = g_hT + (size_t)dt * 32 * 24576;
      h_publish(sbase, cta, lane);
      wait_ge(&g_cnt[C_H * 32], 128);
      fence_proxy_async();
      if (lane == 0) PROF(1);
      int krow = 0, s = 0; uint32_t ph = 1;
      #pragma unroll 1
      for (int kb = 0; kb < 32; kb++) {
        const uint32_t sa = sbase + s * ST1, fb = bars + B_FULL1 + 8 * s;
        if (kb >= 4) mbar_wait(bars + B_EMPTY1 + 8 * s, ph);
        if (kb == 3) mbar_wait(bars + B_WPK, 0);
        if (kb == H1) mbar_wait(bars + B_FULL1, 0);
        if (kb == H2) mbar_wait(bars + B_FULL1 + 8, 0);
        if (elect_one()) {
          if (kb > 0) mbar_expect_tx(fb, ST1);
          bulk_g2s(sa + 16384, Bt, 24576, fb);
          if (kb > 0) {
            tma_2d(sa, &tmW1, f0, krow, fb);
            tma_2d(sa + 8192, &tmW1, f0 + 64, krow, fb);
          }
        }
        __syncwarp();
        krow += 64; Bt += 24576;
        if (++s == 4) { s = 0; ph ^= 1; }
      }
    } else if (cta < 128) {
      h_publish(sbase, cta, lane);
    }
  } else if (warp < 4) {
    if (cta < 128) {
      fft_stage_a(&tmX, sm, sbase, cta, tid - 32);
    }
  } else {
    if (tid == 128) PROF(16);
    if (!fftcta) {
      const int fr = 128 * (cta / 3) + 64 * wg + 16 * wq + (lane >> 2);
      braw0 = ldg16(p.b1 + fr); braw1 = ldg16(p.b1 + fr + 8);
    }
    if (cta < 128) {
      const int rl = 2 * cw + (lane >> 4), cb = lane & 15, row = 16 * cta + rl;
      uint4 xb[5], gw[5];
      #pragma unroll
      for (int i = 0; i < 5; i++) {
        const bool ok = (i < 4) || (cb < 8);
        gw[i] = ok ? ldg128(p.gw + (cb + 16 * i) * 8) : make_uint4(0, 0, 0, 0);
      }
      mbar_wait(bars + B_RAW, 0);
      #pragma unroll
      for (int i = 0; i < 5; i++) {
        const bool ok = (i < 4) || (cb < 8);
        xb[i] = ok ? *reinterpret_cast<const uint4*>(sm + OFF_RAW + rl * 1152 + (cb + 16 * i) * 16) : make_uint4(0, 0, 0, 0);
      }
      float sum = 0.f;
      #pragma unroll
      for (int i = 0; i < 5; i++) {
        const uint32_t w[4] = {xb[i].x, xb[i].y, xb[i].z, xb[i].w};
        #pragma unroll
        for (int j = 0; j < 4; j++) sum += bf_lo(w[j]) + bf_hi(w[j]);
      }
      #pragma unroll
      for (int o = 1; o < 16; o <<= 1) sum += __shfl_xor_sync(0xffffffffu, sum, o);
      const float mean = sum * (1.0f / 576.0f);
      if (ct == 0) PROF(17);
      float vs = 0.f;
      #pragma unroll
      for (int i = 0; i < 5; i++) {
        if ((i < 4) || (cb < 8)) {
          const uint32_t w[4] = {xb[i].x, xb[i].y, xb[i].z, xb[i].w};
          #pragma unroll
          for (int j = 0; j < 4; j++) { float a = bf_lo(w[j]) - mean, b = bf_hi(w[j]) - mean; vs = fmaf(a, a, vs); vs = fmaf(b, b, vs); }
        }
      }
      #pragma unroll
      for (int o = 1; o < 16; o <<= 1) vs += __shfl_xor_sync(0xffffffffu, vs, o);
      const float vb = bf_round(vs * (1.0f / 576.0f));
      const float sd = bf_round(sqrtf(bf_round(vb + 1e-5f)));
      const float rs = 1.0f / sd;
      const uint32_t m2 = pack_bf16(mean, mean);
      const uint32_t hp = sbase + OFF_HST + (rl >> 3) * 3072 + (rl & 7) * 128 + (((lane ^ rl) & 7) << 4);
      #pragma unroll
      for (int i = 0; i < 5; i++) {
        if ((i < 4) || (cb < 8)) {
          const int nb = (cb >> 3) + 2 * i, dt = nb / 3;
          const uint32_t w[4] = {xb[i].x, xb[i].y, xb[i].z, xb[i].w};
          uint32_t o[4];
          #pragma unroll
          for (int j = 0; j < 4; j++) { uint32_t d = bsub2(w[j], m2); o[j] = pack_bf16(bf_lo(d) * rs, bf_hi(d) * rs); }
          sts128(hp + dt * 6144 + (nb - 3 * dt) * 1024, o[0], o[1], o[2], o[3]);
        }
      }
      if (ct == 0) PROF(18);
      bar_arrive(NB_H, 288);
      float gs = 0.f;
      #pragma unroll
      for (int i = 0; i < 5; i++) {
        const uint32_t w[4] = {xb[i].x, xb[i].y, xb[i].z, xb[i].w}, g[4] = {gw[i].x, gw[i].y, gw[i].z, gw[i].w};
        #pragma unroll
        for (int j = 0; j < 4; j++) { uint32_t d = bmul2(w[j], g[j]); gs += bf_lo(d) + bf_hi(d); }
      }
      #pragma unroll
      for (int o = 1; o < 16; o <<= 1) gs += __shfl_xor_sync(0xffffffffu, gs, o);
      if (cb == 0) { float z = bf_round(gs); g_gate[row] = bf_round(1.0f / (1.0f + __expf(-z))); }
    }
    if (ct == 0) PROF(4);
    if (fftcta) {
      tcfft_tab_init(sm + OFF_TAB, ct);
      if (ct == 0) PROF(29);
    }
    if (cta < 128) {
      w_pack(p, &tmWt, sm, sbase, cta, cw, lane);
      if (ct == 0) PROF(27);
      if (fftcta && ct == 0) w_publish(sbase);
    }
  }

  if (!fftcta && warp >= 4) {
    float acc[96];
    int i = 0, s = 0, ps = 0; uint32_t ph = 0;
    do {
      mbar_wait(bars + B_FULL1 + 8 * s, ph);
      if (i == 0 && ct == 0) PROF(5);
      const uint32_t sa = sbase + s * ST1 + wg * 8192, sb = sbase + s * ST1 + 16384;
      wg_fence();
      #pragma unroll
      for (int kk = 0; kk < 4; kk++)
        wgmma_n192(acc, make_desc(sa + kk * 2048, 8192, 1024, 1), make_desc(sb + kk * 6144, 1024, 3072, 1), (kk > 0) ? 1 : i);
      wg_commit();
      wg_wait<1>();
      if (i > 0 && (ct & 127) == 0) mbar_arrive(bars + B_EMPTY1 + 8 * ps);
      if (i == 1 && ct == 0) w_publish(sbase);
      ps = s;
      if (++s == 4) { s = 0; ph ^= 1; }
      i++;
    } while (i < 32);
    wg_wait<0>();
    fence_regs(acc);
    if ((ct & 127) == 0) mbar_arrive(bars + B_G1DONE);
    if (ct == 0) PROF(6);
    mbar_wait(bars + B_ADONE, 0);
    const uint32_t half2 = 0x3f003f00u;
    const uint32_t hb0 = bmul2(braw0 * 0x10001u, half2), hb1 = bmul2(braw1 * 0x10001u, half2);
    const uint32_t a4 = sbase + OFF_STG1 + (uint32_t)wg * 24576 + (uint32_t)wq * 256 + (lane & 7) * 16 + (lane >> 4) * 1024 + ((lane >> 3) & 1) * 128;
    #pragma unroll
    for (int g = 0; g < 24; g += 2) {
      uint32_t o[4];
      #pragma unroll
      for (int q = 0; q < 4; q++) o[q] = bfma2(pack_bf16(acc[4*g + 2*q], acc[4*g + 2*q + 1]), half2, (q & 1) ? hb1 : hb0);
      stsm_x4(a4 + g * 1024, o[0], o[1], o[2], o[3]);
    }
    bar_sync(NB_EPI, 256);
    if (ct == 0) PROF(40);
    uint32_t ea = sbase + OFF_STG1 + ct * 16;
    uint4 v0 = lds128(ea), v1 = lds128(ea + 4096);
    #pragma unroll 1
    for (int j = 0; j < 6; j++) {
      const uint32_t w[8] = {v0.x, v0.y, v0.z, v0.w, v1.x, v1.y, v1.z, v1.w};
      const uint32_t en = ea + ((j < 5) ? 8192 : 0);
      v0 = lds128(en); v1 = lds128(en + 4096);
      float r[16];
      #pragma unroll
      for (int k = 0; k < 16; k++) {
        const float hu = (k & 1) ? bf_hi(w[k >> 1]) : bf_lo(w[k >> 1]);
        r[k] = fmaf(hu, tanh_fast(gelu_arg(hu)), hu);
      }
      sts128(ea, pack_bf16(r[0], r[1]), pack_bf16(r[2], r[3]), pack_bf16(r[4], r[5]), pack_bf16(r[6], r[7]));
      sts128(ea + 4096, pack_bf16(r[8], r[9]), pack_bf16(r[10], r[11]), pack_bf16(r[12], r[13]), pack_bf16(r[14], r[15]));
      __syncwarp();
      if (lane == 0) mbar_arrive(bars + B_UST + 8 * j);
      ea += 8192;
    }
    if (ct == 0) PROF(7);
  }

  if (fftcta) {
    if (tid == 0) { wait_ge(&g_cnt[C_W * 32], 128); wait_ge(&g_cnt[C_X1 * 32], 128); }
    __syncwarp();
    bar_sync(NB_ALL, 384);
    if (tid == 160) PROF(9);
    fence_proxy_async();
    int col = (warp * 24 + (cta - 108) + 1) % 288;
    uint32_t par = 0;
    #pragma unroll 1
    while (true) {
      tcfft_column(col, par);
      if (col != 0) break;
      col = 288; par = 1;
    }
    if (tid == 160) PROF(10);
    bar_sync(NB_ALL, 384);
  }

  if (cta < 128) {
    if (warp == 0) {
      const int m0 = 128 * mt;
      const uint8_t* Tt = g_T + (size_t)(nt * 2 + ks) * 9 * 9216;
      const uint8_t* Ub = g_U + ((size_t)nt * 72 + ks * 36) * 18432;
      if (!fftcta) {
        mbar_wait(bars + B_G1DONE, 0);
        mbar_wait(bars + B_UST + 8 * UWAIT, 0);
      }
      int s = 0, krow = 0; uint32_t ph = 1;
      wait_ge(&g_cnt[C_Z * 32], 32 * NC1 + 4); fence_proxy_async();
      if (lane == 0) PROF(3);
      #pragma unroll 1
      for (int q = 0; q < NC1; q++) {
        const uint32_t sa = sbase + s * ST2, fb = bars + B_FULL2 + 8 * s;
        if (elect_one()) {
          mbar_expect_tx(fb, 16384 + 9216);
          tma_2d(sa, &tmZ, m0, krow, fb);
          tma_2d(sa + 8192, &tmZ, m0 + 64, krow, fb);
          bulk_g2s(sa + 16384, Tt + q * 9216, 9216, fb);
        }
        __syncwarp();
        krow += 64;
        if (++s == 5) { s = 0; ph ^= 1; }
      }
      krow = ks * 2304;
      if (!fftcta) mbar_wait(bars + B_UST + 8 * WWAIT, 0);
      #pragma unroll 1
      for (int m = 0; m < 5; m++) {
        const uint32_t sa = sbase + s * ST2, fb = bars + B_FULL2 + 8 * s;
        if (m == WHOLD) { mbar_wait(bars + B_U1, 0); }
        mbar_wait(bars + B_EMPTY2 + 8 * s, ph);
        if (elect_one()) {
          mbar_expect_tx(fb, ST2);
          tma_2d(sa, &tmW2, m0, krow, fb);
          tma_2d(sa + 8192, &tmW2, m0 + 64, krow, fb);
        }
        __syncwarp();
        krow += 128;
        if (++s == 5) { s = 0; ph ^= 1; }
      }
      const uint8_t* Bt = Ub + 5 * (2 * 18432);
      #pragma unroll 1
      for (int m = 5; m < 36; m++) {
        if (m == 5) fence_proxy_async();
        if (m == 18) {
          mbar_wait(bars + B_U2, 0); fence_proxy_async();
          Bt = Ub + 18432; krow = ks * 2304 + 64;
        }
        const uint32_t sa = sbase + s * ST2, fb = bars + B_FULL2 + 8 * s;
        mbar_wait(bars + B_EMPTY2 + 8 * s, ph);
        if (elect_one()) {
          mbar_expect_tx(fb, ST2);
          tma_2d(sa, &tmW2, m0, krow, fb);
          tma_2d(sa + 8192, &tmW2, m0 + 64, krow, fb);
          bulk_g2s(sa + 16384, Bt, 18432, fb);
        }
        __syncwarp();
        krow += 128; Bt += 2 * 18432;
        if (++s == 5) { s = 0; ph ^= 1; }
      }
      #pragma unroll 1
      for (int n = 0; n < 4; n++) {
        const uint32_t sa = sbase + s * ST2, fb = bars + B_FULL2 + 8 * s;
        mbar_wait(bars + B_EMPTY2 + 8 * s, ph);
        if (elect_one()) {
          mbar_expect_tx(fb, 16384 + 9216 + ((n < 2) ? 8192 : 9216));
          tma_2d(sa, &tmZ, m0, 64 * (3 + n), fb);
          tma_2d(sa + 8192, &tmZ, m0 + 64, 64 * (3 + n), fb);
          bulk_g2s(sa + 16384, Tt + (3 + n) * 9216, 9216, fb);
          if (n < 2) tma_2d(sa + 25600, &tmZ, m0 + 64 * n, 64 * 7, fb);
          else bulk_g2s(sa + 25600, Tt + (5 + n) * 9216, 9216, fb);
        }
        __syncwarp();
        if (++s == 5) { s = 0; ph ^= 1; }
      }
    } else if (warp == 2) {
      if (lane == 0) { asm volatile("prefetch.tensormap [%0];" :: "l"(&tmZ) : "memory"); asm volatile("prefetch.tensormap [%0];" :: "l"(&tmW2) : "memory"); }
      const uint8_t* Ub = g_U + ((size_t)nt * 72 + ks * 36) * 18432;
      if (!fftcta) mbar_wait(bars + B_UST + 8 * 5, 0);
      wait_ge(&g_cnt[C_U * 32], 216); fence_proxy_async();
      if (lane == 0) PROF(2);
      int s = NC1; uint32_t ph = 1;
      #pragma unroll 1
      for (int m = 0; m < 5; m++) {
        mbar_wait(bars + B_EMPTY2 + 8 * s, ph);
        if (elect_one()) bulk_g2s(sbase + s * ST2 + 16384, Ub + m * (2 * 18432), 18432, bars + B_FULL2 + 8 * s);
        __syncwarp();
        if (m == UARR && lane == 0) mbar_arrive(bars + B_U1);
        if (++s == 5) { s = 0; ph ^= 1; }
      }
      wait_ge(&g_cnt[C_U2 * 32], 216); wait_ge(&g_cnt[C_Z2 * 32], 289 - 32 * NC1);
      if (lane == 0) {
        mbar_arrive(bars + B_U2);
        asm volatile("prefetch.tensormap [%0];" :: "l"(&tmOut) : "memory");
        fence_proxy_async();
        mbar_expect_tx(bars + B_Z8, 16384);
        tma_2d(sbase + OFF_STG2, &tmZ, 128 * mt, 512, bars + B_Z8);
        tma_2d(sbase + OFF_STG2 + 9216, &tmZ, 128 * mt + 64, 512, bars + B_Z8);
      }
    } else if (warp == 1 || warp == 3) {
      if (!fftcta) {
        const int mt1 = cta / 3, dt = cta - 3 * mt1;
        #pragma unroll 1
        for (int w = 0; w < 2; w++) {
          const int kb = 2 * mt1 + w, G = 24 * dt + lane;
          const int n_t = (G >= 18) + (G >= 36) + (G >= 54);
          int ng = G - 18 * n_t + ((kb >= 36) ? 9 : 0); ng -= (ng >= 18) ? 18 : 0;
          const bool start = (lane < 24) && ((lane & 7) == 0 || ng == 0 || G == 18 * n_t);
          const uint32_t len = 1024 * __ffs((__ballot_sync(0xffffffffu, start) | 0x1000000u) >> lane >> 1);
          uint8_t* dst = g_U + (size_t)(n_t * 72 + kb) * 18432 + ng * 1024;
          const uint32_t src = sbase + OFF_STG1 + w * 24576 + lane * 1024;
          #pragma unroll 1
          for (int q = (warp >> 1) ^ w; q < 3; q += 2) {
            mbar_wait(bars + B_UST + 8 * (3 * w + q), 0);
            fence_proxy_async_smem();
            if (start && (lane >> 3) == q) bulk_s2g(dst, src, len);
            __syncwarp();
          }
          asm volatile("cp.async.bulk.commit_group;" ::: "memory");
          asm volatile("cp.async.bulk.wait_group 0;" ::: "memory");
          fence_proxy_async();
          __syncwarp();
          if (tid == 32) PROF(30 + w);
          if (lane == 0) red_relaxed(&g_cnt[(w ? C_U2 : C_U) * 32]);
          __syncwarp();
        }
      }
    } else if (warp >= 4) {
      float acc[72], accc[36];
      cluster_wait();
      const int sr = 128 * mt + 64 * wg + 16 * wq + (lane >> 2);
      const float g0 = __ldcg(g_gate + sr), g1 = __ldcg(g_gate + sr + 8);
      braw0 = ldg16(p.b2 + sr); braw1 = ldg16(p.b2 + sr + 8);
      int i = 0, s = 0, ps = 0; uint32_t ph = 0;
      do {
        mbar_wait(bars + B_FULL2 + 8 * s, ph);
        if (i == 0 && ct == 0) PROF(26);
        const uint32_t sa = sbase + s * ST2 + wg * 8192, sb = sbase + s * ST2 + 16384;
        wg_fence();
        #pragma unroll
        for (int kk = 0; kk < 4; kk++)
          wgmma_n72(accc, make_desc(sa + kk * 2048, 8192, 1024, 1), make_desc(sb + kk * 2304, 1152, 128, 0), (kk > 0) ? 1 : i);
        wg_commit();
        wg_wait<1>();
        if (i > 0 && (ct & 127) == 0) mbar_arrive(bars + B_EMPTY2 + 8 * ps);
        ps = s;
        if (++s == 5) { s = 0; ph ^= 1; }
        i++;
      } while (i < NC1);
      wg_wait<0>();
      if ((ct & 127) == 0) mbar_arrive(bars + B_EMPTY2 + 8 * ps);
      i = 0;
      do {
        mbar_wait(bars + B_FULL2 + 8 * s, ph);
        if (i == 0 && ct == 0) PROF(11);
        const uint32_t sa = sbase + s * ST2 + wg * 8192, sb = sbase + s * ST2 + 16384;
        wg_fence();
        #pragma unroll
        for (int kk = 0; kk < 4; kk++)
          wgmma_n144(acc, make_desc(sa + kk * 2048, 8192, 1024, 1), make_desc(sb + kk * 256, 128, 1024, 0), (kk > 0) ? 1 : i);
        wg_commit();
        wg_wait<1>();
        if (i > 0 && (ct & 127) == 0) mbar_arrive(bars + B_EMPTY2 + 8 * ps);
        ps = s;
        if (++s == 5) { s = 0; ph ^= 1; }
        i++;
      } while (i < 36);
      if (ct == 0) PROF(12);
      #pragma unroll
      for (int j = 0; j < 6; j++) {
        uint32_t sa, sb;
        if (j == 3) {
          const int sw = s - 3 + wg, sc = s - 1;
          sa = sbase + ((sw < 0) ? sw + 5 : sw) * ST2 + 25600; sb = sbase + ((sc < 0) ? sc + 5 : sc) * ST2 + 25600;
        } else if (j == 5) {
          const int sc = s - 1;
          sa = sbase + OFF_STG2 + wg * 9216; sb = sbase + ((sc < 0) ? sc + 5 : sc) * ST2 + 25600;
        } else {
          if (j == 0 || j == 4) mbar_wait(bars + B_FULL2 + 8 * s, ph);
          sa = sbase + s * ST2 + wg * 8192; sb = sbase + s * ST2 + 16384;
          if (++s == 5) { s = 0; ph ^= 1; }
        }
        wg_fence();
        #pragma unroll
        for (int kk = 0; kk < 4; kk++)
          wgmma_n72(accc, make_desc(sa + kk * 2048, 8192, 1024, 1), make_desc(sb + kk * 2304, 1152, 128, 0), 1);
        wg_commit();
        if (j == 0) {
          {
            int s2 = s; uint32_t p2 = ph;
            #pragma unroll
            for (int n = 0; n < 2; n++) {
              mbar_wait(bars + B_FULL2 + 8 * s2, p2);
              if (++s2 == 5) { s2 = 0; p2 ^= 1; }
            }
            mbar_wait(bars + B_Z8, 0);
          }
          wg_wait<1>();
          fence_regs(acc);
          const uint32_t xo = mapa(sbase + OFF_XCH + ct * 16, rank ^ 1), xb = mapa(bars + B_XCH, rank ^ 1);
          #pragma unroll
          for (int q = 0; q < 9; q++) st_async128(xo + q * 4096, acc[36 + 4*q], acc[37 + 4*q], acc[38 + 4*q], acc[39 + 4*q], xb);
        }
      }
      const uint32_t bia0 = braw0 * 0x10001u, bia1 = braw1 * 0x10001u;
      const uint32_t gg0 = pack_bf16(g0, g0), gg1 = pack_bf16(g1, g1);
      const uint32_t og0 = pack_bf16(1.0f - g0, 1.0f - g0), og1 = pack_bf16(1.0f - g1, 1.0f - g1);
      uint32_t o[18];
      mbar_wait_cluster(bars + B_XCH, 0);
      if (ct == 0) PROF(14);
      const float4* xi = reinterpret_cast<const float4*>(sm + OFF_XCH) + ct;
      #pragma unroll
      for (int j = 0; j < 9; j++) {
        const float4 v = xi[j * 256];
        o[2*j] = bmul2(og0, badd2(pack_bf16(acc[4*j] + v.x, acc[4*j+1] + v.y), bia0));
        o[2*j+1] = bmul2(og1, badd2(pack_bf16(acc[4*j+2] + v.z, acc[4*j+3] + v.w), bia1));
      }
      wg_wait<0>();
      fence_regs(accc);
      if (ct == 0) PROF(13);
      const float scl = 1.0f / (2.0f * 2048.0f * 576.0f);
      #pragma unroll
      for (int j = 0; j < 9; j++) {
        const uint32_t a0 = pack_bf16(accc[4*j] * scl, accc[4*j+1] * scl), a1 = pack_bf16(accc[4*j+2] * scl, accc[4*j+3] * scl);
        o[2*j] = badd2(bmul2(gg0, a0), o[2*j]);
        o[2*j+1] = badd2(bmul2(gg1, a1), o[2*j+1]);
      }
      bar_sync(NB_EPI + wg * 5, 128);
      const uint32_t stg = sbase + OFF_STG2 + (64 * wg + 16 * wq) * 144;
      {
        const uint32_t a4 = stg + ((lane & 7) + ((lane >> 3) & 1) * 8) * 144 + (lane >> 4) * 16;
        #pragma unroll
        for (int j = 0; j < 8; j += 2) stsm_x4(a4 + j * 16, o[2*j], o[2*j+1], o[2*j+2], o[2*j+3]);
        stsm_x2(stg + ((lane & 7) + ((lane >> 3) & 1) * 8) * 144 + 8 * 16, o[16], o[17]);
      }
      fence_proxy_async_smem();
      __syncwarp();
      if (lane == 0) {
        tma_store_2d(&tmOut, stg, 144 * nt + 72 * ks, 128 * mt + 64 * wg + 16 * wq);
        asm volatile("cp.async.bulk.commit_group;" ::: "memory");
        asm volatile("cp.async.bulk.wait_group.read 0;" ::: "memory");
      }
      __syncwarp();
      if (ct == 0) PROF(15);
    }
  }
  if (warp == 0) {
    if (lane == 0) {
      unsigned old = atomicAdd(&g_cnt[C_EXIT * 32], 1u);
      if (old == NCTA - 1) {
        #pragma unroll 1
        for (int i = 0; i < 8; i++) g_cnt[i * 32] = 0;
      }
    }
  }
  if (warp < 4 || cta >= 128) cluster_wait();
  if (ct == 0) { PROF(61); PROFT(62); }
}

typedef CUresult (*PFN_encodeTiled)(CUtensorMap*, CUtensorMapDataType, cuuint32_t, void*, const cuuint64_t*, const cuuint64_t*,
                                    const cuuint32_t*, const cuuint32_t*, CUtensorMapInterleave, CUtensorMapSwizzle,
                                    CUtensorMapL2promotion, CUtensorMapFloatOOBfill);
static void make_tm(PFN_encodeTiled enc, CUtensorMap* tm, const void* ptr, uint64_t d0, uint64_t d1, uint32_t b0, uint32_t b1, CUtensorMapSwizzle sw, bool w32 = false) {
  cuuint64_t dims[2] = {d0, d1}; cuuint64_t strides[1] = {d0 * (w32 ? 4 : 2)}; cuuint32_t box[2] = {b0, b1}; cuuint32_t es[2] = {1, 1};
  enc(tm, w32 ? CU_TENSOR_MAP_DATA_TYPE_UINT32 : CU_TENSOR_MAP_DATA_TYPE_BFLOAT16, 2, const_cast<void*>(ptr), dims, strides, box, es, CU_TENSOR_MAP_INTERLEAVE_NONE, sw,
      CU_TENSOR_MAP_L2_PROMOTION_L2_128B, CU_TENSOR_MAP_FLOAT_OOB_FILL_NONE);
}
}

extern "C" void kernel_launch(void* const* d_in, const int* in_sizes, int n_in, void* d_out, int out_size) {
  using namespace gm;
  (void)in_sizes; (void)n_in; (void)out_size;
  static PFN_encodeTiled enc = nullptr;
  static void* zT = nullptr;
  static void* x1T = nullptr;
  static void* wT = nullptr;
  if (!enc) {
    void* fn = nullptr; cudaDriverEntryPointQueryResult q;
    cudaGetDriverEntryPoint("cuTensorMapEncodeTiled", &fn, cudaEnableDefault, &q);
    enc = (PFN_encodeTiled)fn;
    cudaGetSymbolAddress(&zT, g_zT);
    cudaGetSymbolAddress(&x1T, g_x1T);
    cudaGetSymbolAddress(&wT, g_wT);
    cudaFuncSetAttribute(fused_kernel, cudaFuncAttributeMaxDynamicSharedMemorySize, SMEM_BYTES);
  }
  CUtensorMap tmW1, tmW2, tmZ, tmOut, tmX, tmWt;
  make_tm(enc, &tmW1, d_in[4], 4608, 2048, 64, 64, CU_TENSOR_MAP_SWIZZLE_128B);
  make_tm(enc, &tmW2, d_in[6], 2048, 4608, 64, 64, CU_TENSOR_MAP_SWIZZLE_128B);
  make_tm(enc, &tmZ, zT, 2048, 576, 64, 64, CU_TENSOR_MAP_SWIZZLE_128B);
  make_tm(enc, &tmOut, d_out, 576, 2048, 72, 16, CU_TENSOR_MAP_SWIZZLE_NONE);
  make_tm(enc, &tmX, x1T, 2048, 289, 16, 146, CU_TENSOR_MAP_SWIZZLE_NONE, true);
  make_tm(enc, &tmWt, wT, 2048, 289, 16, 160, CU_TENSOR_MAP_SWIZZLE_64B, true);
  Params p;
  p.Ax = (const __nv_bfloat16*)d_in[0]; p.Wr = (const __nv_bfloat16*)d_in[1]; p.Wi = (const __nv_bfloat16*)d_in[2];
  p.b1 = (const __nv_bfloat16*)d_in[5]; p.b2 = (const __nv_bfloat16*)d_in[7];
  p.gw = (const __nv_bfloat16*)d_in[8]; p.W1 = (const __nv_bfloat16*)d_in[4];
  cudaLaunchConfig_t cfg = {};
  cfg.gridDim = dim3(NCTA); cfg.blockDim = dim3(384); cfg.dynamicSmemBytes = SMEM_BYTES; cfg.stream = cudaStreamPerThread;
  cudaLaunchAttribute at[1];
  at[0].id = cudaLaunchAttributeClusterDimension; at[0].val.clusterDim.x = 2; at[0].val.clusterDim.y = 1; at[0].val.clusterDim.z = 1;
  cfg.attrs = at; cfg.numAttrs = 1;
  cudaLaunchKernelEx(&cfg, fused_kernel, tmW1, tmW2, tmZ, tmOut, tmX, tmWt, p);
}
```
